```python
import torch

def _softmax(x, axis=-1):
    return torch.softmax(x, dim=axis)
def _gelu(x):
    return torch.nn.functional.gelu(x, approximate="tanh")
def _silu(x):
    return torch.nn.functional.silu(x)
def _sigmoid(x):
    return torch.sigmoid(x)
def _layernorm(x, axis=-1, eps=1e-5):
    m = x.mean(dim=axis, keepdim=True)
    v = x.var(dim=axis, keepdim=True, unbiased=False)
    return (x - m) / torch.sqrt(v + eps)
def _scatter_add(tgt, idx, src, axis=0):
    return tgt.clone().index_add_(axis, idx, src)
def _segment_sum(src, seg, n):
    out = torch.zeros((n,) + src.shape[1:], dtype=src.dtype)
    return out.index_add_(0, seg, src)
def _pad(x, pw):
    flat = tuple(v for pair in reversed(pw) for v in pair)
    return torch.nn.functional.pad(x, flat)

kernel_name = 'gather_scatter__hybrid_graph_tf_graphgps__graph'

def setup_inputs():

    _w = (lambda a: (lambda t: t.to(torch.bfloat16) if t.is_floating_point() else t)(torch.as_tensor(a)))
    N, deg, D = 10000, 16, 128
    E = N * deg
    src = (lambda lo, hi, *s: torch.randint(lo, hi, s))(0, N, E).to(torch.int64)
    dst = (lambda lo, hi, *s: torch.randint(lo, hi, s))(0, N, E).to(torch.int64)
    deg_cnt = torch.bincount(dst, minlength=N).to(float) + 1.0
    sc = 1.0 / float(D) ** 0.5
    return {
        "x": _w((lambda *s: torch.randn(*s, dtype=torch.bfloat16) * 0.05)(N, D)),
        "src": _w(src),
        "dst": _w(dst),
        "deg_inv": _w((1.0 / deg_cnt).to(float)),
        "w_msg": _w((lambda *s: torch.randn(*s, dtype=torch.bfloat16) * 0.2)(D, D) * sc),
        "wq": _w((lambda *s: torch.randn(*s, dtype=torch.bfloat16) * 1.6)(D, D) * sc),
        "wk": _w((lambda *s: torch.randn(*s, dtype=torch.bfloat16) * 1.6)(D, D) * sc),
        "wv": _w((lambda *s: torch.randn(*s, dtype=torch.bfloat16) * 0.2)(D, D) * sc),
        "w_out": _w((lambda *s: torch.randn(*s, dtype=torch.bfloat16) * 0.2)(D, D) * sc),
    }

def reference(x, src, dst, deg_inv, w_msg, wq, wk, wv, w_out):
    N, D = x.shape[0], x.shape[1]
    h = _layernorm(x, axis=-1)
    m_e = torch.einsum('nd,de->ne', h, w_msg)
    h_local = _segment_sum(m_e[src], dst, N) * deg_inv[:, None]
    q = torch.einsum('nd,de->ne', h, wq)
    k = torch.einsum('nd,de->ne', h, wk)
    v = torch.einsum('nd,de->ne', h, wv)
    logits = torch.einsum('id,jd->ij', q, k) / (float(D) ** 0.5)
    attn = _softmax(logits, axis=-1)
    h_global = torch.einsum('ij,jd->id', attn, v)
    y = torch.einsum('nd,de->ne', h_local + h_global, w_out)
    return x + y
```

```cpp
#include <cuda_runtime.h>
#include <cuda_bf16.h>
#include <cuda_fp16.h>
#include <stdint.h>

namespace {

constexpr int REGC = 224;
constexpr int REGB = (504 - 2 * REGC);
constexpr int EXP1 = 48;
constexpr int EXP2 = 40;
constexpr int EXP3 = 40;
constexpr int KG = 2;
constexpr int GS = 34;
constexpr int PWAIT = 500;

constexpr int NN = 10000;
constexpr int EE = 160000;
constexpr int NCTA = 132;
constexpr int ROWS_B = 8448;
constexpr int NSLABX = 97;
constexpr int CAP = 56;
constexpr int NLT = 127;
constexpr int NLC = 4;

constexpr float KV_A = 5.6f;
constexpr float KV_C0 = 4.0f;
constexpr float QSCALE = 1.4426950408889634f * 0.08838834764831845f / KV_A;
constexpr float PSHIFT = -24.0f;
constexpr float BOUND = 96.0f;
constexpr float NORM2_MAX = BOUND * BOUND / (KV_A * KV_A * 128.0f * 1.03f * 1.03f);

constexpr uint32_t SB0 = 1024;
constexpr int SLOT = 36864;
constexpr int SM_RING = 0;
constexpr int SM_PARK = 4 * SLOT;
constexpr int SM_MU = SM_PARK + 32768;
constexpr int SM_RECV = SM_MU + 2048;
constexpr int SM_XR = SM_RECV + 16384;
constexpr int SM_RX = SM_PARK + 24576;
constexpr int SM_XS = SM_RECV + 32768;
constexpr int SM_BAR = SM_XS + 12288;
constexpr int B_FULL = SM_BAR, B_EMPTY = SM_BAR + 32, B_G = SM_BAR + 64, B_DEC = SM_BAR + 72, B_STAGED = SM_BAR + 80,
              B_AGG = SM_BAR + 88, B_REQ = SM_BAR + 96, B_RECV = SM_BAR + 104, B_W2 = SM_BAR + 112, B_LD = SM_BAR + 120,
              B_RFREE = SM_BAR + 128, B_RS = SM_BAR + 136, B_XD = SM_BAR + 144, B_FIN = SM_BAR + 152, B_QB = SM_BAR + 1800;
constexpr int SM_FLAGS = SM_BAR + 160;
constexpr int SM_C = SM_FLAGS + 52;
constexpr int SM_CMD = SM_FLAGS + 56;
constexpr int SM_PST = SM_BAR + 224;
constexpr int SM_BST = SM_BAR + 240;
constexpr int SM_RS = SM_BAR + 256;
constexpr int SM_MEAN = SM_BAR + 1280;
constexpr int SM_SH = SM_BAR + 1664;
constexpr int SM_R2 = SM_BAR + 1728;
constexpr int SM_TOTAL = SM_BAR + 2048;
constexpr int SM_WQ = SM_RING + SLOT, SM_WK = SM_WQ + 32768, SM_XB = SM_WQ + 49152, SM_XA = SM_RING + 3 * SLOT;
constexpr int PART_BYTES = 32768 + 2048;
enum { CMD_DONE = 0, CMD_M = 2, CMD_L, CMD_W0, CMD_W1 };

constexpr int EPC = 1224, INBOX = 131 * 128;
struct Scratch {
    uint8_t kv[NN * 256];
    unsigned long long h1[64 * 16];
    unsigned int b, l1, l2, done, ovf, ql, cw, pad2[25];
    unsigned int a[12], pad3[20];
    unsigned int Lmax[16], pad4[16];
    uint8_t pad5[640];
    float rsx[2048];
    uint8_t w2p[2 * 32768];
    uint8_t qL[4096 + 128];
    float Lacc[NLC * 16 * 128];
    uint8_t inbox[NCTA * INBOX];
    uint8_t h16[(NN + 1) * 256];
    uint8_t part[NCTA * PART_BYTES];
    int2 ovfl[EE];
};
__device__ __align__(1024) uint8_t g_raw[sizeof(Scratch) + (2 << 20) + 1024];

template <int O = 0, int L>
__device__ __forceinline__ void wgmma_rs128_k(float (&d)[L], uint32_t a0, uint32_t a1, uint32_t a2, uint32_t a3, uint64_t descB) {
    asm volatile("wgmma.mma_async.sync.aligned.m64n128k16.f32.bf16.bf16 {"
        "%0, %1, %2, %3, %4, %5, %6, %7, %8, %9, %10, %11, %12, %13, %14, %15, %16, %17, %18, %19, %20, %21, %22, %23, %24, %25, %26, %27, "
        "%28, %29, %30, %31, %32, %33, %34, %35, %36, %37, %38, %39, %40, %41, %42, %43, %44, %45, %46, %47, %48, %49, %50, %51, %52, %53, "
        "%54, %55, %56, %57, %58, %59, %60, %61, %62, %63"
        "}, {%64, %65, %66, %67}, %68, 1, 1, 1, 0;"
        : "+f"(d[0]), "+f"(d[1]), "+f"(d[2]), "+f"(d[3]), "+f"(d[4]), "+f"(d[5]), "+f"(d[6]), "+f"(d[7]), "+f"(d[8]), "+f"(d[9]),
          "+f"(d[10]), "+f"(d[11]), "+f"(d[12]), "+f"(d[13]), "+f"(d[14]), "+f"(d[15]), "+f"(d[16]), "+f"(d[17]), "+f"(d[18]), "+f"(d[19]),
          "+f"(d[20]), "+f"(d[21]), "+f"(d[22]), "+f"(d[23]), "+f"(d[24]), "+f"(d[25]), "+f"(d[26]), "+f"(d[27]), "+f"(d[28]), "+f"(d[29]),
          "+f"(d[30]), "+f"(d[31]), "+f"(d[32]), "+f"(d[33]), "+f"(d[34]), "+f"(d[35]), "+f"(d[36]), "+f"(d[37]), "+f"(d[38]), "+f"(d[39]),
          "+f"(d[40]), "+f"(d[41]), "+f"(d[42]), "+f"(d[43]), "+f"(d[44]), "+f"(d[45]), "+f"(d[46]), "+f"(d[47]), "+f"(d[48]), "+f"(d[49]),
          "+f"(d[50]), "+f"(d[51]), "+f"(d[52]), "+f"(d[53]), "+f"(d[54]), "+f"(d[55]), "+f"(d[56]), "+f"(d[57]), "+f"(d[58]), "+f"(d[59]),
          "+f"(d[60]), "+f"(d[61]), "+f"(d[62]), "+f"(d[63])
        : "r"(a0), "r"(a1), "r"(a2), "r"(a3), "l"(descB));
}
template <int O = 0, int L>
__device__ __forceinline__ void wgmma_rs144_k(float (&d)[L], uint32_t a0, uint32_t a1, uint32_t a2, uint32_t a3, uint64_t descB) {
    asm volatile("wgmma.mma_async.sync.aligned.m64n144k16.f32.bf16.bf16 {"
        "%0, %1, %2, %3, %4, %5, %6, %7, %8, %9, %10, %11, %12, %13, %14, %15, %16, %17, %18, %19, %20, %21, %22, %23, %24, %25, %26, %27, "
        "%28, %29, %30, %31, %32, %33, %34, %35, %36, %37, %38, %39, %40, %41, %42, %43, %44, %45, %46, %47, %48, %49, %50, %51, %52, %53, "
        "%54, %55, %56, %57, %58, %59, %60, %61, %62, %63, %64, %65, %66, %67, %68, %69, %70, %71"
        "}, {%72, %73, %74, %75}, %76, 1, 1, 1, 0;"
        : "+f"(d[0]), "+f"(d[1]), "+f"(d[2]), "+f"(d[3]), "+f"(d[4]), "+f"(d[5]), "+f"(d[6]), "+f"(d[7]), "+f"(d[8]), "+f"(d[9]),
          "+f"(d[10]), "+f"(d[11]), "+f"(d[12]), "+f"(d[13]), "+f"(d[14]), "+f"(d[15]), "+f"(d[16]), "+f"(d[17]), "+f"(d[18]), "+f"(d[19]),
          "+f"(d[20]), "+f"(d[21]), "+f"(d[22]), "+f"(d[23]), "+f"(d[24]), "+f"(d[25]), "+f"(d[26]), "+f"(d[27]), "+f"(d[28]), "+f"(d[29]),
          "+f"(d[30]), "+f"(d[31]), "+f"(d[32]), "+f"(d[33]), "+f"(d[34]), "+f"(d[35]), "+f"(d[36]), "+f"(d[37]), "+f"(d[38]), "+f"(d[39]),
          "+f"(d[40]), "+f"(d[41]), "+f"(d[42]), "+f"(d[43]), "+f"(d[44]), "+f"(d[45]), "+f"(d[46]), "+f"(d[47]), "+f"(d[48]), "+f"(d[49]),
          "+f"(d[50]), "+f"(d[51]), "+f"(d[52]), "+f"(d[53]), "+f"(d[54]), "+f"(d[55]), "+f"(d[56]), "+f"(d[57]), "+f"(d[58]), "+f"(d[59]),
          "+f"(d[60]), "+f"(d[61]), "+f"(d[62]), "+f"(d[63]), "+f"(d[64]), "+f"(d[65]), "+f"(d[66]), "+f"(d[67]), "+f"(d[68]), "+f"(d[69]),
          "+f"(d[70]), "+f"(d[71])
        : "r"(a0), "r"(a1), "r"(a2), "r"(a3), "l"(descB));
}
template <int O = 0, int L>
__device__ __forceinline__ void wgmma_rs128_mn(float (&d)[L], uint32_t a0, uint32_t a1, uint32_t a2, uint32_t a3, uint64_t descB) {
    asm volatile("wgmma.mma_async.sync.aligned.m64n128k16.f32.bf16.bf16 {"
        "%0, %1, %2, %3, %4, %5, %6, %7, %8, %9, %10, %11, %12, %13, %14, %15, %16, %17, %18, %19, %20, %21, %22, %23, %24, %25, %26, %27, "
        "%28, %29, %30, %31, %32, %33, %34, %35, %36, %37, %38, %39, %40, %41, %42, %43, %44, %45, %46, %47, %48, %49, %50, %51, %52, %53, "
        "%54, %55, %56, %57, %58, %59, %60, %61, %62, %63"
        "}, {%64, %65, %66, %67}, %68, 1, 1, 1, 1;"
        : "+f"(d[0]), "+f"(d[1]), "+f"(d[2]), "+f"(d[3]), "+f"(d[4]), "+f"(d[5]), "+f"(d[6]), "+f"(d[7]), "+f"(d[8]), "+f"(d[9]),
          "+f"(d[10]), "+f"(d[11]), "+f"(d[12]), "+f"(d[13]), "+f"(d[14]), "+f"(d[15]), "+f"(d[16]), "+f"(d[17]), "+f"(d[18]), "+f"(d[19]),
          "+f"(d[20]), "+f"(d[21]), "+f"(d[22]), "+f"(d[23]), "+f"(d[24]), "+f"(d[25]), "+f"(d[26]), "+f"(d[27]), "+f"(d[28]), "+f"(d[29]),
          "+f"(d[30]), "+f"(d[31]), "+f"(d[32]), "+f"(d[33]), "+f"(d[34]), "+f"(d[35]), "+f"(d[36]), "+f"(d[37]), "+f"(d[38]), "+f"(d[39]),
          "+f"(d[40]), "+f"(d[41]), "+f"(d[42]), "+f"(d[43]), "+f"(d[44]), "+f"(d[45]), "+f"(d[46]), "+f"(d[47]), "+f"(d[48]), "+f"(d[49]),
          "+f"(d[50]), "+f"(d[51]), "+f"(d[52]), "+f"(d[53]), "+f"(d[54]), "+f"(d[55]), "+f"(d[56]), "+f"(d[57]), "+f"(d[58]), "+f"(d[59]),
          "+f"(d[60]), "+f"(d[61]), "+f"(d[62]), "+f"(d[63])
        : "r"(a0), "r"(a1), "r"(a2), "r"(a3), "l"(descB));
}
template <int O = 0, int L>
__device__ __forceinline__ void wgmma_ss128_k(float (&d)[L], uint64_t descA, uint64_t descB) {
    asm volatile("wgmma.mma_async.sync.aligned.m64n128k16.f32.bf16.bf16 {"
        "%0, %1, %2, %3, %4, %5, %6, %7, %8, %9, %10, %11, %12, %13, %14, %15, %16, %17, %18, %19, %20, %21, %22, %23, %24, %25, %26, %27, "
        "%28, %29, %30, %31, %32, %33, %34, %35, %36, %37, %38, %39, %40, %41, %42, %43, %44, %45, %46, %47, %48, %49, %50, %51, %52, %53, "
        "%54, %55, %56, %57, %58, %59, %60, %61, %62, %63"
        "}, %64, %65, 1, 1, 1, 0, 0;"
        : "+f"(d[0]), "+f"(d[1]), "+f"(d[2]), "+f"(d[3]), "+f"(d[4]), "+f"(d[5]), "+f"(d[6]), "+f"(d[7]), "+f"(d[8]), "+f"(d[9]),
          "+f"(d[10]), "+f"(d[11]), "+f"(d[12]), "+f"(d[13]), "+f"(d[14]), "+f"(d[15]), "+f"(d[16]), "+f"(d[17]), "+f"(d[18]), "+f"(d[19]),
          "+f"(d[20]), "+f"(d[21]), "+f"(d[22]), "+f"(d[23]), "+f"(d[24]), "+f"(d[25]), "+f"(d[26]), "+f"(d[27]), "+f"(d[28]), "+f"(d[29]),
          "+f"(d[30]), "+f"(d[31]), "+f"(d[32]), "+f"(d[33]), "+f"(d[34]), "+f"(d[35]), "+f"(d[36]), "+f"(d[37]), "+f"(d[38]), "+f"(d[39]),
          "+f"(d[40]), "+f"(d[41]), "+f"(d[42]), "+f"(d[43]), "+f"(d[44]), "+f"(d[45]), "+f"(d[46]), "+f"(d[47]), "+f"(d[48]), "+f"(d[49]),
          "+f"(d[50]), "+f"(d[51]), "+f"(d[52]), "+f"(d[53]), "+f"(d[54]), "+f"(d[55]), "+f"(d[56]), "+f"(d[57]), "+f"(d[58]), "+f"(d[59]),
          "+f"(d[60]), "+f"(d[61]), "+f"(d[62]), "+f"(d[63])
        : "l"(descA), "l"(descB));
}
template <int O = 0, int L>
__device__ __forceinline__ void wgmma_ss144_k(float (&d)[L], uint64_t descA, uint64_t descB) {
    asm volatile("wgmma.mma_async.sync.aligned.m64n144k16.f32.bf16.bf16 {"
        "%0, %1, %2, %3, %4, %5, %6, %7, %8, %9, %10, %11, %12, %13, %14, %15, %16, %17, %18, %19, %20, %21, %22, %23, %24, %25, %26, %27, "
        "%28, %29, %30, %31, %32, %33, %34, %35, %36, %37, %38, %39, %40, %41, %42, %43, %44, %45, %46, %47, %48, %49, %50, %51, %52, %53, "
        "%54, %55, %56, %57, %58, %59, %60, %61, %62, %63, %64, %65, %66, %67, %68, %69, %70, %71"
        "}, %72, %73, 1, 1, 1, 0, 0;"
        : "+f"(d[0]), "+f"(d[1]), "+f"(d[2]), "+f"(d[3]), "+f"(d[4]), "+f"(d[5]), "+f"(d[6]), "+f"(d[7]), "+f"(d[8]), "+f"(d[9]),
          "+f"(d[10]), "+f"(d[11]), "+f"(d[12]), "+f"(d[13]), "+f"(d[14]), "+f"(d[15]), "+f"(d[16]), "+f"(d[17]), "+f"(d[18]), "+f"(d[19]),
          "+f"(d[20]), "+f"(d[21]), "+f"(d[22]), "+f"(d[23]), "+f"(d[24]), "+f"(d[25]), "+f"(d[26]), "+f"(d[27]), "+f"(d[28]), "+f"(d[29]),
          "+f"(d[30]), "+f"(d[31]), "+f"(d[32]), "+f"(d[33]), "+f"(d[34]), "+f"(d[35]), "+f"(d[36]), "+f"(d[37]), "+f"(d[38]), "+f"(d[39]),
          "+f"(d[40]), "+f"(d[41]), "+f"(d[42]), "+f"(d[43]), "+f"(d[44]), "+f"(d[45]), "+f"(d[46]), "+f"(d[47]), "+f"(d[48]), "+f"(d[49]),
          "+f"(d[50]), "+f"(d[51]), "+f"(d[52]), "+f"(d[53]), "+f"(d[54]), "+f"(d[55]), "+f"(d[56]), "+f"(d[57]), "+f"(d[58]), "+f"(d[59]),
          "+f"(d[60]), "+f"(d[61]), "+f"(d[62]), "+f"(d[63]), "+f"(d[64]), "+f"(d[65]), "+f"(d[66]), "+f"(d[67]), "+f"(d[68]), "+f"(d[69]),
          "+f"(d[70]), "+f"(d[71])
        : "l"(descA), "l"(descB));
}
template <int O = 0, int L>
__device__ __forceinline__ void wgmma_rs128_k_i(float (&d)[L], uint32_t a0, uint32_t a1, uint32_t a2, uint32_t a3, uint64_t descB) {
    asm volatile("wgmma.mma_async.sync.aligned.m64n128k16.f32.bf16.bf16 {"
        "%0, %1, %2, %3, %4, %5, %6, %7, %8, %9, %10, %11, %12, %13, %14, %15, %16, %17, %18, %19, %20, %21, %22, %23, %24, %25, %26, %27, "
        "%28, %29, %30, %31, %32, %33, %34, %35, %36, %37, %38, %39, %40, %41, %42, %43, %44, %45, %46, %47, %48, %49, %50, %51, %52, %53, "
        "%54, %55, %56, %57, %58, %59, %60, %61, %62, %63"
        "}, {%64, %65, %66, %67}, %68, 0, 1, 1, 0;"
        : "=f"(d[0]), "=f"(d[1]), "=f"(d[2]), "=f"(d[3]), "=f"(d[4]), "=f"(d[5]), "=f"(d[6]), "=f"(d[7]), "=f"(d[8]), "=f"(d[9]),
          "=f"(d[10]), "=f"(d[11]), "=f"(d[12]), "=f"(d[13]), "=f"(d[14]), "=f"(d[15]), "=f"(d[16]), "=f"(d[17]), "=f"(d[18]), "=f"(d[19]),
          "=f"(d[20]), "=f"(d[21]), "=f"(d[22]), "=f"(d[23]), "=f"(d[24]), "=f"(d[25]), "=f"(d[26]), "=f"(d[27]), "=f"(d[28]), "=f"(d[29]),
          "=f"(d[30]), "=f"(d[31]), "=f"(d[32]), "=f"(d[33]), "=f"(d[34]), "=f"(d[35]), "=f"(d[36]), "=f"(d[37]), "=f"(d[38]), "=f"(d[39]),
          "=f"(d[40]), "=f"(d[41]), "=f"(d[42]), "=f"(d[43]), "=f"(d[44]), "=f"(d[45]), "=f"(d[46]), "=f"(d[47]), "=f"(d[48]), "=f"(d[49]),
          "=f"(d[50]), "=f"(d[51]), "=f"(d[52]), "=f"(d[53]), "=f"(d[54]), "=f"(d[55]), "=f"(d[56]), "=f"(d[57]), "=f"(d[58]), "=f"(d[59]),
          "=f"(d[60]), "=f"(d[61]), "=f"(d[62]), "=f"(d[63])
        : "r"(a0), "r"(a1), "r"(a2), "r"(a3), "l"(descB));
}
template <int O = 0, int L>
__device__ __forceinline__ void wgmma_rs144_k_i(float (&d)[L], uint32_t a0, uint32_t a1, uint32_t a2, uint32_t a3, uint64_t descB) {
    asm volatile("wgmma.mma_async.sync.aligned.m64n144k16.f32.bf16.bf16 {"
        "%0, %1, %2, %3, %4, %5, %6, %7, %8, %9, %10, %11, %12, %13, %14, %15, %16, %17, %18, %19, %20, %21, %22, %23, %24, %25, %26, %27, "
        "%28, %29, %30, %31, %32, %33, %34, %35, %36, %37, %38, %39, %40, %41, %42, %43, %44, %45, %46, %47, %48, %49, %50, %51, %52, %53, "
        "%54, %55, %56, %57, %58, %59, %60, %61, %62, %63, %64, %65, %66, %67, %68, %69, %70, %71"
        "}, {%72, %73, %74, %75}, %76, 0, 1, 1, 0;"
        : "=f"(d[0]), "=f"(d[1]), "=f"(d[2]), "=f"(d[3]), "=f"(d[4]), "=f"(d[5]), "=f"(d[6]), "=f"(d[7]), "=f"(d[8]), "=f"(d[9]),
          "=f"(d[10]), "=f"(d[11]), "=f"(d[12]), "=f"(d[13]), "=f"(d[14]), "=f"(d[15]), "=f"(d[16]), "=f"(d[17]), "=f"(d[18]), "=f"(d[19]),
          "=f"(d[20]), "=f"(d[21]), "=f"(d[22]), "=f"(d[23]), "=f"(d[24]), "=f"(d[25]), "=f"(d[26]), "=f"(d[27]), "=f"(d[28]), "=f"(d[29]),
          "=f"(d[30]), "=f"(d[31]), "=f"(d[32]), "=f"(d[33]), "=f"(d[34]), "=f"(d[35]), "=f"(d[36]), "=f"(d[37]), "=f"(d[38]), "=f"(d[39]),
          "=f"(d[40]), "=f"(d[41]), "=f"(d[42]), "=f"(d[43]), "=f"(d[44]), "=f"(d[45]), "=f"(d[46]), "=f"(d[47]), "=f"(d[48]), "=f"(d[49]),
          "=f"(d[50]), "=f"(d[51]), "=f"(d[52]), "=f"(d[53]), "=f"(d[54]), "=f"(d[55]), "=f"(d[56]), "=f"(d[57]), "=f"(d[58]), "=f"(d[59]),
          "=f"(d[60]), "=f"(d[61]), "=f"(d[62]), "=f"(d[63]), "=f"(d[64]), "=f"(d[65]), "=f"(d[66]), "=f"(d[67]), "=f"(d[68]), "=f"(d[69]),
          "=f"(d[70]), "=f"(d[71])
        : "r"(a0), "r"(a1), "r"(a2), "r"(a3), "l"(descB));
}
template <int O = 0, int L>
__device__ __forceinline__ void wgmma_rs128_mn_i(float (&d)[L], uint32_t a0, uint32_t a1, uint32_t a2, uint32_t a3, uint64_t descB) {
    asm volatile("wgmma.mma_async.sync.aligned.m64n128k16.f32.bf16.bf16 {"
        "%0, %1, %2, %3, %4, %5, %6, %7, %8, %9, %10, %11, %12, %13, %14, %15, %16, %17, %18, %19, %20, %21, %22, %23, %24, %25, %26, %27, "
        "%28, %29, %30, %31, %32, %33, %34, %35, %36, %37, %38, %39, %40, %41, %42, %43, %44, %45, %46, %47, %48, %49, %50, %51, %52, %53, "
        "%54, %55, %56, %57, %58, %59, %60, %61, %62, %63"
        "}, {%64, %65, %66, %67}, %68, 0, 1, 1, 1;"
        : "=f"(d[0]), "=f"(d[1]), "=f"(d[2]), "=f"(d[3]), "=f"(d[4]), "=f"(d[5]), "=f"(d[6]), "=f"(d[7]), "=f"(d[8]), "=f"(d[9]),
          "=f"(d[10]), "=f"(d[11]), "=f"(d[12]), "=f"(d[13]), "=f"(d[14]), "=f"(d[15]), "=f"(d[16]), "=f"(d[17]), "=f"(d[18]), "=f"(d[19]),
          "=f"(d[20]), "=f"(d[21]), "=f"(d[22]), "=f"(d[23]), "=f"(d[24]), "=f"(d[25]), "=f"(d[26]), "=f"(d[27]), "=f"(d[28]), "=f"(d[29]),
          "=f"(d[30]), "=f"(d[31]), "=f"(d[32]), "=f"(d[33]), "=f"(d[34]), "=f"(d[35]), "=f"(d[36]), "=f"(d[37]), "=f"(d[38]), "=f"(d[39]),
          "=f"(d[40]), "=f"(d[41]), "=f"(d[42]), "=f"(d[43]), "=f"(d[44]), "=f"(d[45]), "=f"(d[46]), "=f"(d[47]), "=f"(d[48]), "=f"(d[49]),
          "=f"(d[50]), "=f"(d[51]), "=f"(d[52]), "=f"(d[53]), "=f"(d[54]), "=f"(d[55]), "=f"(d[56]), "=f"(d[57]), "=f"(d[58]), "=f"(d[59]),
          "=f"(d[60]), "=f"(d[61]), "=f"(d[62]), "=f"(d[63])
        : "r"(a0), "r"(a1), "r"(a2), "r"(a3), "l"(descB));
}
template <int O = 0, int L>
__device__ __forceinline__ void wgmma_ss128_k_i(float (&d)[L], uint64_t descA, uint64_t descB) {
    asm volatile("wgmma.mma_async.sync.aligned.m64n128k16.f32.bf16.bf16 {"
        "%0, %1, %2, %3, %4, %5, %6, %7, %8, %9, %10, %11, %12, %13, %14, %15, %16, %17, %18, %19, %20, %21, %22, %23, %24, %25, %26, %27, "
        "%28, %29, %30, %31, %32, %33, %34, %35, %36, %37, %38, %39, %40, %41, %42, %43, %44, %45, %46, %47, %48, %49, %50, %51, %52, %53, "
        "%54, %55, %56, %57, %58, %59, %60, %61, %62, %63"
        "}, %64, %65, 0, 1, 1, 0, 0;"
        : "=f"(d[0]), "=f"(d[1]), "=f"(d[2]), "=f"(d[3]), "=f"(d[4]), "=f"(d[5]), "=f"(d[6]), "=f"(d[7]), "=f"(d[8]), "=f"(d[9]),
          "=f"(d[10]), "=f"(d[11]), "=f"(d[12]), "=f"(d[13]), "=f"(d[14]), "=f"(d[15]), "=f"(d[16]), "=f"(d[17]), "=f"(d[18]), "=f"(d[19]),
          "=f"(d[20]), "=f"(d[21]), "=f"(d[22]), "=f"(d[23]), "=f"(d[24]), "=f"(d[25]), "=f"(d[26]), "=f"(d[27]), "=f"(d[28]), "=f"(d[29]),
          "=f"(d[30]), "=f"(d[31]), "=f"(d[32]), "=f"(d[33]), "=f"(d[34]), "=f"(d[35]), "=f"(d[36]), "=f"(d[37]), "=f"(d[38]), "=f"(d[39]),
          "=f"(d[40]), "=f"(d[41]), "=f"(d[42]), "=f"(d[43]), "=f"(d[44]), "=f"(d[45]), "=f"(d[46]), "=f"(d[47]), "=f"(d[48]), "=f"(d[49]),
          "=f"(d[50]), "=f"(d[51]), "=f"(d[52]), "=f"(d[53]), "=f"(d[54]), "=f"(d[55]), "=f"(d[56]), "=f"(d[57]), "=f"(d[58]), "=f"(d[59]),
          "=f"(d[60]), "=f"(d[61]), "=f"(d[62]), "=f"(d[63])
        : "l"(descA), "l"(descB));
}
template <int O = 0, int L>
__device__ __forceinline__ void wgmma_ss144_k_i(float (&d)[L], uint64_t descA, uint64_t descB) {
    asm volatile("wgmma.mma_async.sync.aligned.m64n144k16.f32.bf16.bf16 {"
        "%0, %1, %2, %3, %4, %5, %6, %7, %8, %9, %10, %11, %12, %13, %14, %15, %16, %17, %18, %19, %20, %21, %22, %23, %24, %25, %26, %27, "
        "%28, %29, %30, %31, %32, %33, %34, %35, %36, %37, %38, %39, %40, %41, %42, %43, %44, %45, %46, %47, %48, %49, %50, %51, %52, %53, "
        "%54, %55, %56, %57, %58, %59, %60, %61, %62, %63, %64, %65, %66, %67, %68, %69, %70, %71"
        "}, %72, %73, 0, 1, 1, 0, 0;"
        : "=f"(d[0]), "=f"(d[1]), "=f"(d[2]), "=f"(d[3]), "=f"(d[4]), "=f"(d[5]), "=f"(d[6]), "=f"(d[7]), "=f"(d[8]), "=f"(d[9]),
          "=f"(d[10]), "=f"(d[11]), "=f"(d[12]), "=f"(d[13]), "=f"(d[14]), "=f"(d[15]), "=f"(d[16]), "=f"(d[17]), "=f"(d[18]), "=f"(d[19]),
          "=f"(d[20]), "=f"(d[21]), "=f"(d[22]), "=f"(d[23]), "=f"(d[24]), "=f"(d[25]), "=f"(d[26]), "=f"(d[27]), "=f"(d[28]), "=f"(d[29]),
          "=f"(d[30]), "=f"(d[31]), "=f"(d[32]), "=f"(d[33]), "=f"(d[34]), "=f"(d[35]), "=f"(d[36]), "=f"(d[37]), "=f"(d[38]), "=f"(d[39]),
          "=f"(d[40]), "=f"(d[41]), "=f"(d[42]), "=f"(d[43]), "=f"(d[44]), "=f"(d[45]), "=f"(d[46]), "=f"(d[47]), "=f"(d[48]), "=f"(d[49]),
          "=f"(d[50]), "=f"(d[51]), "=f"(d[52]), "=f"(d[53]), "=f"(d[54]), "=f"(d[55]), "=f"(d[56]), "=f"(d[57]), "=f"(d[58]), "=f"(d[59]),
          "=f"(d[60]), "=f"(d[61]), "=f"(d[62]), "=f"(d[63]), "=f"(d[64]), "=f"(d[65]), "=f"(d[66]), "=f"(d[67]), "=f"(d[68]), "=f"(d[69]),
          "=f"(d[70]), "=f"(d[71])
        : "l"(descA), "l"(descB));
}
template <int O = 0, int L>
__device__ __forceinline__ void wgmma_ss16_k(float (&d)[L], uint64_t descA, uint64_t descB) {
    asm volatile("wgmma.mma_async.sync.aligned.m64n16k16.f32.bf16.bf16 {"
        "%0, %1, %2, %3, %4, %5, %6, %7"
        "}, %8, %9, 1, 1, 1, 0, 0;"
        : "+f"(d[O + 0]), "+f"(d[O + 1]), "+f"(d[O + 2]), "+f"(d[O + 3]), "+f"(d[O + 4]), "+f"(d[O + 5]), "+f"(d[O + 6]), "+f"(d[O + 7])
        : "l"(descA), "l"(descB));
}
template <int O = 0, int L>
__device__ __forceinline__ void wgmma_ss16_k_i(float (&d)[L], uint64_t descA, uint64_t descB) {
    asm volatile("wgmma.mma_async.sync.aligned.m64n16k16.f32.bf16.bf16 {"
        "%0, %1, %2, %3, %4, %5, %6, %7"
        "}, %8, %9, 0, 1, 1, 0, 0;"
        : "=f"(d[O + 0]), "=f"(d[O + 1]), "=f"(d[O + 2]), "=f"(d[O + 3]), "=f"(d[O + 4]), "=f"(d[O + 5]), "=f"(d[O + 6]), "=f"(d[O + 7])
        : "l"(descA), "l"(descB));
}
template <int O = 0, int L>
__device__ __forceinline__ void wgmma_ss16_m(float (&d)[L], uint64_t descA, uint64_t descB) {
    asm volatile("wgmma.mma_async.sync.aligned.m64n16k16.f32.bf16.bf16 {"
        "%0, %1, %2, %3, %4, %5, %6, %7"
        "}, %8, %9, 1, 1, 1, 1, 0;"
        : "+f"(d[O + 0]), "+f"(d[O + 1]), "+f"(d[O + 2]), "+f"(d[O + 3]), "+f"(d[O + 4]), "+f"(d[O + 5]), "+f"(d[O + 6]), "+f"(d[O + 7])
        : "l"(descA), "l"(descB));
}
template <int O = 0, int L>
__device__ __forceinline__ void wgmma_ss16_m_i(float (&d)[L], uint64_t descA, uint64_t descB) {
    asm volatile("wgmma.mma_async.sync.aligned.m64n16k16.f32.bf16.bf16 {"
        "%0, %1, %2, %3, %4, %5, %6, %7"
        "}, %8, %9, 0, 1, 1, 1, 0;"
        : "=f"(d[O + 0]), "=f"(d[O + 1]), "=f"(d[O + 2]), "=f"(d[O + 3]), "=f"(d[O + 4]), "=f"(d[O + 5]), "=f"(d[O + 6]), "=f"(d[O + 7])
        : "l"(descA), "l"(descB));
}
template <int O = 0, int L>
__device__ __forceinline__ void wgmma_ss32_m(float (&d)[L], uint64_t descA, uint64_t descB) {
    asm volatile("wgmma.mma_async.sync.aligned.m64n32k16.f32.bf16.bf16 {"
        "%0, %1, %2, %3, %4, %5, %6, %7, %8, %9, %10, %11, %12, %13, %14, %15"
        "}, %16, %17, 1, 1, 1, 1, 0;"
        : "+f"(d[0]), "+f"(d[1]), "+f"(d[2]), "+f"(d[3]), "+f"(d[4]), "+f"(d[5]), "+f"(d[6]), "+f"(d[7]), "+f"(d[8]), "+f"(d[9]),
          "+f"(d[10]), "+f"(d[11]), "+f"(d[12]), "+f"(d[13]), "+f"(d[14]), "+f"(d[15])
        : "l"(descA), "l"(descB));
}
template <int O = 0, int L>
__device__ __forceinline__ void wgmma_ss128_mn(float (&d)[L], uint64_t descA, uint64_t descB) {
    asm volatile("wgmma.mma_async.sync.aligned.m64n128k16.f32.bf16.bf16 {"
        "%0, %1, %2, %3, %4, %5, %6, %7, %8, %9, %10, %11, %12, %13, %14, %15, %16, %17, %18, %19, %20, %21, %22, %23, %24, %25, %26, %27, "
        "%28, %29, %30, %31, %32, %33, %34, %35, %36, %37, %38, %39, %40, %41, %42, %43, %44, %45, %46, %47, %48, %49, %50, %51, %52, %53, "
        "%54, %55, %56, %57, %58, %59, %60, %61, %62, %63"
        "}, %64, %65, 1, 1, 1, 0, 1;"
        : "+f"(d[0]), "+f"(d[1]), "+f"(d[2]), "+f"(d[3]), "+f"(d[4]), "+f"(d[5]), "+f"(d[6]), "+f"(d[7]), "+f"(d[8]), "+f"(d[9]),
          "+f"(d[10]), "+f"(d[11]), "+f"(d[12]), "+f"(d[13]), "+f"(d[14]), "+f"(d[15]), "+f"(d[16]), "+f"(d[17]), "+f"(d[18]), "+f"(d[19]),
          "+f"(d[20]), "+f"(d[21]), "+f"(d[22]), "+f"(d[23]), "+f"(d[24]), "+f"(d[25]), "+f"(d[26]), "+f"(d[27]), "+f"(d[28]), "+f"(d[29]),
          "+f"(d[30]), "+f"(d[31]), "+f"(d[32]), "+f"(d[33]), "+f"(d[34]), "+f"(d[35]), "+f"(d[36]), "+f"(d[37]), "+f"(d[38]), "+f"(d[39]),
          "+f"(d[40]), "+f"(d[41]), "+f"(d[42]), "+f"(d[43]), "+f"(d[44]), "+f"(d[45]), "+f"(d[46]), "+f"(d[47]), "+f"(d[48]), "+f"(d[49]),
          "+f"(d[50]), "+f"(d[51]), "+f"(d[52]), "+f"(d[53]), "+f"(d[54]), "+f"(d[55]), "+f"(d[56]), "+f"(d[57]), "+f"(d[58]), "+f"(d[59]),
          "+f"(d[60]), "+f"(d[61]), "+f"(d[62]), "+f"(d[63])
        : "l"(descA), "l"(descB));
}
template <int O = 0, int L>
__device__ __forceinline__ void wgmma_ss32_m_i(float (&d)[L], uint64_t descA, uint64_t descB) {
    asm volatile("wgmma.mma_async.sync.aligned.m64n32k16.f32.bf16.bf16 {"
        "%0, %1, %2, %3, %4, %5, %6, %7, %8, %9, %10, %11, %12, %13, %14, %15"
        "}, %16, %17, 0, 1, 1, 1, 0;"
        : "=f"(d[0]), "=f"(d[1]), "=f"(d[2]), "=f"(d[3]), "=f"(d[4]), "=f"(d[5]), "=f"(d[6]), "=f"(d[7]), "=f"(d[8]), "=f"(d[9]),
          "=f"(d[10]), "=f"(d[11]), "=f"(d[12]), "=f"(d[13]), "=f"(d[14]), "=f"(d[15])
        : "l"(descA), "l"(descB));
}
template <int O = 0, int L>
__device__ __forceinline__ void wgmma_ss128_mn_i(float (&d)[L], uint64_t descA, uint64_t descB) {
    asm volatile("wgmma.mma_async.sync.aligned.m64n128k16.f32.bf16.bf16 {"
        "%0, %1, %2, %3, %4, %5, %6, %7, %8, %9, %10, %11, %12, %13, %14, %15, %16, %17, %18, %19, %20, %21, %22, %23, %24, %25, %26, %27, "
        "%28, %29, %30, %31, %32, %33, %34, %35, %36, %37, %38, %39, %40, %41, %42, %43, %44, %45, %46, %47, %48, %49, %50, %51, %52, %53, "
        "%54, %55, %56, %57, %58, %59, %60, %61, %62, %63"
        "}, %64, %65, 0, 1, 1, 0, 1;"
        : "=f"(d[0]), "=f"(d[1]), "=f"(d[2]), "=f"(d[3]), "=f"(d[4]), "=f"(d[5]), "=f"(d[6]), "=f"(d[7]), "=f"(d[8]), "=f"(d[9]),
          "=f"(d[10]), "=f"(d[11]), "=f"(d[12]), "=f"(d[13]), "=f"(d[14]), "=f"(d[15]), "=f"(d[16]), "=f"(d[17]), "=f"(d[18]), "=f"(d[19]),
          "=f"(d[20]), "=f"(d[21]), "=f"(d[22]), "=f"(d[23]), "=f"(d[24]), "=f"(d[25]), "=f"(d[26]), "=f"(d[27]), "=f"(d[28]), "=f"(d[29]),
          "=f"(d[30]), "=f"(d[31]), "=f"(d[32]), "=f"(d[33]), "=f"(d[34]), "=f"(d[35]), "=f"(d[36]), "=f"(d[37]), "=f"(d[38]), "=f"(d[39]),
          "=f"(d[40]), "=f"(d[41]), "=f"(d[42]), "=f"(d[43]), "=f"(d[44]), "=f"(d[45]), "=f"(d[46]), "=f"(d[47]), "=f"(d[48]), "=f"(d[49]),
          "=f"(d[50]), "=f"(d[51]), "=f"(d[52]), "=f"(d[53]), "=f"(d[54]), "=f"(d[55]), "=f"(d[56]), "=f"(d[57]), "=f"(d[58]), "=f"(d[59]),
          "=f"(d[60]), "=f"(d[61]), "=f"(d[62]), "=f"(d[63])
        : "l"(descA), "l"(descB));
}
template <int O = 0, int L>
__device__ __forceinline__ void wgmma_rs128_mn_z(float (&d)[L], uint32_t a0, uint32_t a1, uint32_t a2, uint32_t a3, uint64_t descB) {
    asm volatile("wgmma.mma_async.sync.aligned.m64n128k16.f32.bf16.bf16 {"
        "%0, %1, %2, %3, %4, %5, %6, %7, %8, %9, %10, %11, %12, %13, %14, %15, %16, %17, %18, %19, %20, %21, %22, %23, %24, %25, %26, %27, "
        "%28, %29, %30, %31, %32, %33, %34, %35, %36, %37, %38, %39, %40, %41, %42, %43, %44, %45, %46, %47, %48, %49, %50, %51, %52, %53, "
        "%54, %55, %56, %57, %58, %59, %60, %61, %62, %63"
        "}, {%64, %65, %66, %67}, %68, 0, 1, 1, 1;"
        : "+f"(d[0]), "+f"(d[1]), "+f"(d[2]), "+f"(d[3]), "+f"(d[4]), "+f"(d[5]), "+f"(d[6]), "+f"(d[7]), "+f"(d[8]), "+f"(d[9]),
          "+f"(d[10]), "+f"(d[11]), "+f"(d[12]), "+f"(d[13]), "+f"(d[14]), "+f"(d[15]), "+f"(d[16]), "+f"(d[17]), "+f"(d[18]), "+f"(d[19]),
          "+f"(d[20]), "+f"(d[21]), "+f"(d[22]), "+f"(d[23]), "+f"(d[24]), "+f"(d[25]), "+f"(d[26]), "+f"(d[27]), "+f"(d[28]), "+f"(d[29]),
          "+f"(d[30]), "+f"(d[31]), "+f"(d[32]), "+f"(d[33]), "+f"(d[34]), "+f"(d[35]), "+f"(d[36]), "+f"(d[37]), "+f"(d[38]), "+f"(d[39]),
          "+f"(d[40]), "+f"(d[41]), "+f"(d[42]), "+f"(d[43]), "+f"(d[44]), "+f"(d[45]), "+f"(d[46]), "+f"(d[47]), "+f"(d[48]), "+f"(d[49]),
          "+f"(d[50]), "+f"(d[51]), "+f"(d[52]), "+f"(d[53]), "+f"(d[54]), "+f"(d[55]), "+f"(d[56]), "+f"(d[57]), "+f"(d[58]), "+f"(d[59]),
          "+f"(d[60]), "+f"(d[61]), "+f"(d[62]), "+f"(d[63])
        : "r"(a0), "r"(a1), "r"(a2), "r"(a3), "l"(descB));
}
template <int O = 0, int L>
__device__ __forceinline__ void wgmma_rs16_k(float (&d)[L], uint32_t a0, uint32_t a1, uint32_t a2, uint32_t a3, uint64_t descB) {
    asm volatile("wgmma.mma_async.sync.aligned.m64n16k16.f32.bf16.bf16 {"
        "%0, %1, %2, %3, %4, %5, %6, %7"
        "}, {%8, %9, %10, %11}, %12, 1, 1, 1, 0;"
        : "+f"(d[O + 0]), "+f"(d[O + 1]), "+f"(d[O + 2]), "+f"(d[O + 3]), "+f"(d[O + 4]), "+f"(d[O + 5]), "+f"(d[O + 6]), "+f"(d[O + 7])
        : "r"(a0), "r"(a1), "r"(a2), "r"(a3), "l"(descB));
}

__device__ __forceinline__ void mbar_init(uint32_t bar, int cnt) { asm volatile("mbarrier.init.shared::cta.b64 [%0], %1;" ::"r"(bar), "r"(cnt) : "memory"); }
__device__ __forceinline__ void mbar_expect_tx(uint32_t bar, uint32_t bytes) { asm volatile("mbarrier.arrive.expect_tx.shared::cta.b64 _, [%0], %1;" ::"r"(bar), "r"(bytes) : "memory"); }
__device__ __forceinline__ void mbar_arrive(uint32_t bar) { asm volatile("mbarrier.arrive.shared::cta.b64 _, [%0];" ::"r"(bar) : "memory"); }
__device__ __forceinline__ void mbar_wait(uint32_t bar, uint32_t parity) {
    asm volatile("{\n.reg .pred p;\nLAB_WAIT:\nmbarrier.try_wait.parity.shared::cta.b64 p, [%0], %1;\n@!p bra LAB_WAIT;\n}\n" ::"r"(bar), "r"(parity) : "memory");
}
__device__ __forceinline__ void mbar_wait_b(uint32_t bar, uint32_t parity) {
    asm volatile("{\n.reg .pred p;\n.reg .u32 c;\n"
                 "mbarrier.try_wait.parity.shared::cta.b64 p, [%0], %1;\n@p bra LAB_DONE;\nmov.u32 c, 0;\n"
                 "LAB_WAIT:\nmbarrier.try_wait.parity.shared::cta.b64 p, [%0], %1;\n@p bra LAB_DONE;\n"
                 "add.u32 c, c, 1;\nsetp.lt.u32 p, c, 134217728;\n@p bra LAB_WAIT;\ntrap;\nLAB_DONE:\n}\n" ::"r"(bar), "r"(parity) : "memory");
}
__device__ __forceinline__ void mbar_wait_cl(uint32_t bar, uint32_t parity) {
    mbar_wait(bar, parity);
    asm volatile("fence.acquire.sync_restrict::shared::cluster.cluster;" ::: "memory");
}
__device__ __forceinline__ bool mbar_test(uint32_t bar, uint32_t parity) {
    uint32_t ok;
    asm volatile("{\n.reg .pred p;\nmbarrier.test_wait.parity.shared::cta.b64 p, [%1], %2;\nselp.u32 %0, 1, 0, p;\n}\n" : "=r"(ok) : "r"(bar), "r"(parity) : "memory");
    return ok;
}
__device__ __forceinline__ bool mbar_try(uint32_t bar, uint32_t parity, uint32_t ns) {
    uint32_t ok;
    asm volatile("{\n.reg .pred p;\nmbarrier.try_wait.parity.shared::cta.b64 p, [%1], %2, %3;\nselp.u32 %0, 1, 0, p;\n}\n" : "=r"(ok) : "r"(bar), "r"(parity), "r"(ns) : "memory");
    return ok;
}
__device__ __forceinline__ void mbar_arrive_remote(uint32_t rbar) { asm volatile("mbarrier.arrive.shared::cluster.b64 _, [%0];" ::"r"(rbar) : "memory"); }
__device__ __forceinline__ void poll_ge(const unsigned int* p, unsigned int target) {
    asm volatile("{\n.reg .pred p;\n.reg .u32 c, v;\nmov.u32 c, 0;\n"
                 "LAB_POLL:\nld.relaxed.gpu.global.u32 v, [%0];\nsetp.ge.u32 p, v, %1;\n@p bra LAB_DONE;\nnanosleep.u32 200;\n"
                 "add.u32 c, c, 1;\nsetp.lt.u32 p, c, 33554432;\n@p bra LAB_POLL;\ntrap;\nLAB_DONE:\nfence.acquire.gpu;\n}\n" ::"l"(p), "r"(target) : "memory");
}
__device__ __forceinline__ void poll_cnt(const unsigned long long* p, uint16_t target) {
    asm volatile("{\n.reg .pred p;\n.reg .u32 c;\n.reg .u16 v;\nmov.u32 c, 0;\n"
                 "LAB_POLL:\nld.relaxed.gpu.global.u16 v, [%0];\nsetp.ge.u16 p, v, %1;\n@p bra LAB_DONE;\n"
                 "add.u32 c, c, 1;\nsetp.lt.u32 p, c, 40000000;\n@p bra LAB_POLL;\ntrap;\nLAB_DONE:\nfence.acquire.gpu;\nfence.proxy.async.global;\n}\n" ::"l"(p), "h"(target) : "memory");
}
__device__ __forceinline__ void red_release_u32(unsigned int* p, unsigned int v) { asm volatile("red.release.gpu.global.add.u32 [%0], %1;" ::"l"(p), "r"(v) : "memory"); }
__device__ __forceinline__ void cp16(uint32_t dst, const void* src) { asm volatile("cp.async.cg.shared.global [%0], [%1], 16;" ::"r"(dst), "l"(src) : "memory"); }
__device__ __forceinline__ void cp_commit() { asm volatile("cp.async.commit_group;" ::: "memory"); }
template <int n> __device__ __forceinline__ void cp_wait() { asm volatile("cp.async.wait_group %0;" ::"n"(n) : "memory"); }
__device__ __forceinline__ void bulk_s2g(void* dst, uint32_t src, uint32_t bytes) {
    asm volatile("cp.async.bulk.global.shared::cta.bulk_group [%0], [%1], %2;" ::"l"(dst), "r"(src), "r"(bytes) : "memory");
}
__device__ __forceinline__ void bulk_wait_all() { asm volatile("cp.async.bulk.commit_group;\ncp.async.bulk.wait_group 0;" ::: "memory"); }
__device__ __forceinline__ void bulk_g2s(uint32_t dst, const void* src, uint32_t bytes, uint32_t bar) {
    asm volatile("cp.async.bulk.shared::cluster.global.mbarrier::complete_tx::bytes [%0], [%1], %2, [%3];" ::"r"(dst), "l"(src), "r"(bytes), "r"(bar) : "memory");
}
__device__ __forceinline__ void bulk_s2c(uint32_t rdst, uint32_t src, uint32_t bytes, uint32_t rbar) {
    asm volatile("cp.async.bulk.shared::cluster.shared::cta.mbarrier::complete_tx::bytes [%0], [%1], %2, [%3];" ::"r"(rdst), "r"(src), "r"(bytes), "r"(rbar) : "memory");
}
__device__ __forceinline__ uint32_t mapa(uint32_t a, uint32_t rank) { uint32_t r; asm("mapa.shared::cluster.u32 %0, %1, %2;" : "=r"(r) : "r"(a), "r"(rank)); return r; }
__device__ __forceinline__ void fence_async_smem() { asm volatile("fence.proxy.async.shared::cta;" ::: "memory"); }
__device__ __forceinline__ void fence_async_global() { asm volatile("fence.proxy.async.global;" ::: "memory"); }
__device__ __forceinline__ void cluster_arrive_relaxed() { asm volatile("barrier.cluster.arrive.relaxed.aligned;" ::: "memory"); }
__device__ __forceinline__ void cluster_wait() { asm volatile("barrier.cluster.wait.acquire.aligned;" ::: "memory"); }
__device__ __forceinline__ void wgmma_fence() { asm volatile("wgmma.fence.sync.aligned;" ::: "memory"); }
__device__ __forceinline__ void wgmma_commit() { asm volatile("wgmma.commit_group.sync.aligned;" ::: "memory"); }
template <int n> __device__ __forceinline__ void wgmma_wait() { asm volatile("wgmma.wait_group.sync.aligned %0;" ::"n"(n) : "memory"); }
__device__ __forceinline__ void bar_sync(int id, int cnt) { asm volatile("bar.sync %0, %1;" ::"r"(id), "r"(cnt) : "memory"); }
__device__ __forceinline__ void bar_arrive(int id, int cnt) { asm volatile("bar.arrive %0, %1;" ::"r"(id), "r"(cnt) : "memory"); }
__device__ __forceinline__ void rejoin() { bar_sync(10 + ((threadIdx.x >> 5) & 3), 32); }
template <int n, int L> __device__ __forceinline__ void pin(float (&d)[L]) {
#pragma unroll
    for (int i = 0; i < n; i++) asm volatile("" : "+f"(d[i])::"memory");
}
template <int n, int L> __device__ __forceinline__ void pin(uint32_t (&d)[L]) {
#pragma unroll
    for (int i = 0; i < n; i++) asm volatile("" : "+r"(d[i])::"memory");
}
__device__ __forceinline__ float ex2(float x) { float y; asm("ex2.approx.ftz.f32 %0, %1;" : "=f"(y) : "f"(x)); return y; }
__device__ __forceinline__ uint32_t pack2(float lo, float hi) { uint32_t r; asm("cvt.rn.bf16x2.f32 %0, %1, %2;" : "=r"(r) : "f"(hi), "f"(lo)); return r; }
__device__ __forceinline__ float blo(uint32_t v) { return __uint_as_float(v << 16); }
__device__ __forceinline__ float bhi(uint32_t v) { return __uint_as_float(v & 0xffff0000u); }
__device__ __forceinline__ int uni(int v) { return __shfl_sync(~0u, v, 0); }
__device__ __forceinline__ float quad_sum(float v) { v += __shfl_xor_sync(~0u, v, 1); v += __shfl_xor_sync(~0u, v, 2); return v; }
__device__ __forceinline__ float quad_max(float v) { v = fmaxf(v, __shfl_xor_sync(~0u, v, 1)); v = fmaxf(v, __shfl_xor_sync(~0u, v, 2)); return v; }
__device__ __forceinline__ void sts128(uint32_t a, uint32_t x, uint32_t y, uint32_t z, uint32_t w) { asm volatile("st.shared.v4.b32 [%0], {%1,%2,%3,%4};" ::"r"(a), "r"(x), "r"(y), "r"(z), "r"(w) : "memory"); }
__device__ __forceinline__ uint4 lds128(uint32_t a) { uint4 v; asm volatile("ld.shared.v4.b32 {%0,%1,%2,%3}, [%4];" : "=r"(v.x), "=r"(v.y), "=r"(v.z), "=r"(v.w) : "r"(a) : "memory"); return v; }
__device__ __forceinline__ void sts32(uint32_t a, uint32_t v) { asm volatile("st.shared.b32 [%0], %1;" ::"r"(a), "r"(v) : "memory"); }
__device__ __forceinline__ uint32_t lds32(uint32_t a) { uint32_t v; asm volatile("ld.shared.b32 %0, [%1];" : "=r"(v) : "r"(a) : "memory"); return v; }
__device__ __forceinline__ uint32_t atoms_inc(uint32_t a) { uint32_t v; asm volatile("atom.shared.add.u32 %0, [%1], 1;" : "=r"(v) : "r"(a) : "memory"); return v; }
__device__ __forceinline__ uint32_t atoms_inc_if(uint32_t a, uint32_t cond) {
    uint32_t v = 255;
    asm volatile("{\n.reg .pred p;\nsetp.ne.u32 p, %2, 0;\n@p atom.shared.add.u32 %0, [%1], 1;\n}" : "+r"(v) : "r"(a), "r"(cond) : "memory");
    return v;
}
__device__ __forceinline__ uint4 ldsm4(uint32_t a) { uint4 v; asm volatile("ldmatrix.sync.aligned.m8n8.x4.shared.b16 {%0,%1,%2,%3}, [%4];" : "=r"(v.x), "=r"(v.y), "=r"(v.z), "=r"(v.w) : "r"(a) : "memory"); return v; }
__device__ __forceinline__ void stsm4(uint32_t a, uint32_t x, uint32_t y, uint32_t z, uint32_t w) {
    asm volatile("stmatrix.sync.aligned.m8n8.x4.shared.b16 [%0], {%1,%2,%3,%4};" ::"r"(a), "r"(x), "r"(y), "r"(z), "r"(w) : "memory");
}
__device__ __forceinline__ void stsm4t(uint32_t a, uint32_t x, uint32_t y, uint32_t z, uint32_t w) {
    asm volatile("stmatrix.sync.aligned.m8n8.x4.trans.shared.b16 [%0], {%1,%2,%3,%4};" ::"r"(a), "r"(x), "r"(y), "r"(z), "r"(w) : "memory");
}
__device__ __forceinline__ float2 lds64f(uint32_t a) { float2 v; asm volatile("ld.shared.v2.f32 {%0,%1}, [%2];" : "=f"(v.x), "=f"(v.y) : "r"(a) : "memory"); return v; }
__device__ __forceinline__ __half2 h2(uint32_t v) { return *reinterpret_cast<const __half2*>(&v); }
__device__ __forceinline__ float half_sum(float v) {
#pragma unroll
    for (int i = 1; i < 16; i *= 2) v += __shfl_xor_sync(~0u, v, i);
    return v;
}
__device__ __forceinline__ float safe_div(float a, float b) { return __fdividef(a, b * 0.0009765625f) * 0.0009765625f; }
__device__ __forceinline__ uint32_t comp(const uint4& v, int j) { return j == 0 ? v.x : j == 1 ? v.y : j == 2 ? v.z : v.w; }

__device__ __forceinline__ uint32_t swz(int row, int chunk) {
    return (uint32_t)((row >> 3) * 2048 + (chunk >> 3) * 1024 + (row & 7) * 128 + (((chunk & 7) ^ (row & 7)) << 4));
}
__device__ __forceinline__ uint64_t desc_k(uint32_t addr) {
    return (uint64_t)((addr + SB0) >> 4) | (1ull << 16) | ((uint64_t)(2048 >> 4) << 32) | (1ull << 62);
}
__device__ __forceinline__ uint64_t desc_mn(uint32_t addr) {
    return (uint64_t)((addr + SB0) >> 4) | ((uint64_t)(1024 >> 4) << 16) | ((uint64_t)(2048 >> 4) << 32) | (1ull << 62);
}
__device__ __forceinline__ uint64_t desc_pn(uint32_t addr) {
    return (uint64_t)((addr + SB0) >> 4) | ((uint64_t)(16384 >> 4) << 16) | ((uint64_t)(1024 >> 4) << 32) | (1ull << 62);
}
__device__ __forceinline__ uint64_t rt(uint64_t d) { d += blockIdx.y; asm volatile("" : "+l"(d)); return d; }
__device__ __forceinline__ constexpr uint64_t koff(int k) { return (uint64_t)(((k >> 2) * 1024 + (k & 3) * 32) >> 4); }

template <bool WIDE, int L>
__device__ __forceinline__ void issue_qk(float (&s)[L], const uint32_t (&q)[32], uint64_t dk) {
    if constexpr (WIDE) wgmma_rs144_k_i(s, q[0], q[1], q[2], q[3], dk);
    else wgmma_rs128_k_i(s, q[0], q[1], q[2], q[3], dk);
#pragma unroll
    for (int k = 1; k < 8; k++) {
        if constexpr (WIDE) wgmma_rs144_k(s, q[4 * k], q[4 * k + 1], q[4 * k + 2], q[4 * k + 3], dk + koff(k));
        else wgmma_rs128_k(s, q[4 * k], q[4 * k + 1], q[4 * k + 2], q[4 * k + 3], dk + koff(k));
    }
}
template <int KSTEP = 256, int L>
__device__ __forceinline__ void issue_pv(float (&o)[L], const uint32_t (&p)[36], uint64_t dv) {
#pragma unroll
    for (int k = 0; k < 8; k++) wgmma_rs128_mn(o, p[4 * k], p[4 * k + 1], p[4 * k + 2], p[4 * k + 3], dv + (uint64_t)(k * KSTEP));
}

template <int L>
__device__ __forceinline__ void row_sums(const float (&s)[L], float& m0, float& m1) {
    float a0 = s[0], a1 = s[1], b0 = s[2], b1 = s[3];
#pragma unroll
    for (int i = 4; i < 64; i += 4) { a0 += s[i]; a1 += s[i + 1]; b0 += s[i + 2]; b1 += s[i + 3]; }
    m0 = a0 + a1; m1 = b0 + b1;
}
__device__ __forceinline__ void st_async4(uint32_t rdst, uint32_t x, uint32_t y, uint32_t z, uint32_t w, uint32_t rbar) {
    asm volatile("st.async.shared::cluster.mbarrier::complete_tx::bytes.v4.b32 [%0], {%1,%2,%3,%4}, [%5];" ::"r"(rdst), "r"(x), "r"(y), "r"(z), "r"(w), "r"(rbar) : "memory");
}
__device__ __forceinline__ float norm4(const uint32_t (&q)[32], int i0) {
    uint32_t a;
    asm("mul.rn.bf16x2 %0, %1, %1;" : "=r"(a) : "r"(q[i0]));
#pragma unroll
    for (int i = 1; i < 4; i++) asm("fma.rn.bf16x2 %0, %1, %1, %0;" : "+r"(a) : "r"(q[i0 + 2 * i]));
    return blo(a) + bhi(a);
}
__device__ __forceinline__ bool unsafe_norms(float n0, float n1) {
    return __any_sync(~0u, !(quad_sum(n0) * 1.02f <= NORM2_MAX) | !(quad_sum(n1) * 1.02f <= NORM2_MAX));
}
__device__ __forceinline__ bool unsafe_rows(const uint32_t (&q)[32]) {
    float n0 = 0.f, n1 = 0.f;
#pragma unroll
    for (int k = 0; k < 4; k++) { n0 += norm4(q, 8 * k); n1 += norm4(q, 8 * k + 1); }
    return unsafe_norms(n0, n1);
}
__device__ __forceinline__ uint32_t read_flags(uint32_t sb) {
    uint4 a = lds128(sb + SM_FLAGS), b = lds128(sb + SM_FLAGS + 16), c = lds128(sb + SM_FLAGS + 32);
    return a.x | a.y | a.z | a.w | b.x | b.y | b.z | b.w | c.x | c.y | c.z | c.w | lds32(sb + SM_FLAGS + 48);
}

#define DERIVE                                                                                                              \
    int tid, b;                                                                                                             \
    asm volatile("mov.u32 %0, %%tid.x;" : "=r"(tid));                                                                       \
    asm volatile("mov.u32 %0, %%ctaid.x;" : "=r"(b));                                                                       \
    [[maybe_unused]] const uint32_t sb = SB0 + ((b & 1) << 24);                                                             \
    [[maybe_unused]] const int lane = tid & 31, warp = (tid >> 5) & 3, gq = lane >> 2, t = lane & 3, rank = b & 1, rowX = ROWS_B + 16 * b; \
    [[maybe_unused]] const int w = warp - 1, bt = tid - 288, l16 = lane & 15, hi = lane >> 4;                               \
    [[maybe_unused]] const bool isW = b >= 128, isQ = b == NSLABX - 1;

#define DERIVE_SC                                                                                                           \
    DERIVE                                                                                                                  \
    size_t scv_ = __cvta_generic_to_global(sc0);                                                                            \
    asm volatile("" : "+l"(scv_));                                                                                          \
    [[maybe_unused]] Scratch* const sc = reinterpret_cast<Scratch*>(__cvta_global_to_generic(scv_));

struct Cons {
    uint32_t sb;
    int myid, otherid;
    bool lane0;
    uint32_t flag;
};

__device__ __forceinline__ void sched_fence() { asm volatile("pmevent 0;" ::: "memory"); }
template <int BEG, int CNT, bool SAFE>
__device__ __forceinline__ void do_exp(float (&s)[72], float m0, float m1) {
#pragma unroll
    for (int i = BEG; i < CNT; i += 4) {
        if constexpr (SAFE) { s[i] -= m0; s[i + 1] -= m0; s[i + 2] -= m1; s[i + 3] -= m1; }
        s[i] = ex2(s[i]); s[i + 1] = ex2(s[i + 1]); s[i + 2] = ex2(s[i + 2]); s[i + 3] = ex2(s[i + 3]);
    }
}
template <int CNT>
__device__ __forceinline__ void do_pack(const float (&s)[72], uint32_t (&p)[36], bool tail) {
#pragma unroll
    for (int i = 0; i < CNT / 2; i++) {
        p[i] = pack2(s[2 * i], s[2 * i + 1]);
        if (i >= 32 && !tail) p[i] = 0u;
    }
}
__device__ __forceinline__ void load_q(uint32_t (&q)[32], uint32_t base, int lane) {
#pragma unroll
    for (int k = 0; k < 8; k++) {
        uint4 v = ldsm4(base + swz(lane & 15, 2 * k + (lane >> 4)));
        q[4 * k] = v.x; q[4 * k + 1] = v.y; q[4 * k + 2] = v.z; q[4 * k + 3] = v.w;
    }
}

template <int MODE, bool SAFE>
__device__ __forceinline__ void step(const Cons& c, int it, float (&s)[72], float (&o)[64], uint32_t (&p)[36], uint32_t (&q)[32],
                                     float m0, float m1, bool tail) {
    constexpr int CNT = 64;
    const int sl = it & 3, ps = (it + 3) & 3;
    if constexpr (MODE < 2) mbar_wait_b(c.sb + B_FULL + 8 * sl, (it >> 2) & 1); else mbar_wait(c.sb + B_FULL + 8 * sl, (it >> 2) & 1);
    bar_sync(c.myid, 256);
    if constexpr (MODE == 3) pin<36>(p);
    else { pin<32>(p); pin<64>(o); }
    wgmma_fence();
    if constexpr (MODE == 2) {
        const uint64_t da = rt(desc_k(SM_PARK + (__shfl_sync(~0u, threadIdx.x, 0) >> 7) * 16384)), db = rt(desc_k(SM_RING + sl * SLOT));
        wgmma_ss144_k_i(s, da, db);
#pragma unroll
        for (int k = 1; k < 8; k++) wgmma_ss144_k(s, da + koff(k), db + koff(k));
    } else {
        issue_qk<false>(s, q, rt(desc_k(SM_RING + sl * SLOT)));
    }
    wgmma_commit();
    if constexpr (MODE == 3) sched_fence();
    if constexpr (MODE == 2) {
        issue_pv(o, p, desc_mn(SM_RING + ps * SLOT));
        wgmma_commit();
        bar_arrive(c.otherid, 256);
        DERIVE
        const uint32_t park = sb + SM_PARK + (tid >> 5) * 4096;
        wgmma_wait<1>();
        pin<72>(s);
        do_exp<64, 72, SAFE>(s, m0, m1);
#pragma unroll
        for (int i = 32; i < 36; i++) { p[i] = tail ? pack2(s[2 * i], s[2 * i + 1]) : 0u; asm volatile("" : "+r"(p[i])); }
        sched_fence();
        load_q(q, park, lane);
        do_exp<0, EXP2, SAFE>(s, m0, m1);
        pin<EXP2>(s);
        sched_fence();
        wgmma_wait<0>();
        pin<64>(o); pin<32>(p); pin<64>(s);
        if (c.lane0) mbar_arrive(c.sb + B_EMPTY + 8 * ps);
        do_exp<EXP2, 64, SAFE>(s, m0, m1);
    } else {
        if constexpr (MODE == 3) {
            DERIVE
            const uint32_t a = sb + SM_PARK + (tid >> 5) * 4096 + lane * 16;
            const float u0 = 0.5f * (o[0] + o[33]), u1 = 0.5f * (o[2] + o[35]);
#pragma unroll
            for (int k = 0; k < 8; k++)
                sts128(a + k * 512, pack2(o[8 * k] - u0, o[8 * k + 1] - u0), pack2(o[8 * k + 2] - u1, o[8 * k + 3] - u1),
                       pack2(o[8 * k + 4] - u0, o[8 * k + 5] - u0), pack2(o[8 * k + 6] - u1, o[8 * k + 7] - u1));
            asm volatile("st.shared.v2.f32 [%0], {%1, %2};" ::"r"(sb + SM_MU + tid * 8), "f"(u0), "f"(u1) : "memory");
            pin<64>(o);
            wgmma_fence();
            wgmma_rs128_mn_z(o, p[32], p[33], p[34], p[35], desc_mn(SM_RING + ps * SLOT + 32768));
        }
        issue_pv(o, p, desc_mn(SM_RING + ps * SLOT));
        wgmma_commit();
        bar_arrive(c.otherid, 256);
        if constexpr (MODE == 3) { fence_async_smem(); __syncwarp(); if (c.lane0) mbar_arrive(c.sb + B_STAGED); }
        wgmma_wait<1>();
        pin<CNT>(s);
        do_exp<0, EXP1, SAFE>(s, m0, m1);
        pin<EXP1>(s);
        sched_fence();
        wgmma_wait<0>();
        pin<64>(o); pin<32>(p); pin<CNT>(s);
        if (c.lane0) mbar_arrive(c.sb + B_EMPTY + 8 * ps);
        do_exp<EXP1, CNT, SAFE>(s, m0, m1);
    }
    do_pack<CNT>(s, p, tail);
}
template <int BEG>
__device__ __forceinline__ void q_move(uint32_t (&q)[32]) {
    uint32_t zero;
    asm volatile("mov.u32 %0, %%ctaid.y;" : "=r"(zero));
#pragma unroll
    for (int i = BEG; i < 32; i++) q[i] ^= zero;
}

template <bool SAFE>
__device__ __forceinline__ void first_steps(const Cons& c, int it, float (&s)[72], float (&o)[64], uint32_t (&p)[36], uint32_t (&q)[32],
                                            float m0, float m1, bool tail) {
    const int sl = it & 3, ns = (it + 1) & 3;
    mbar_wait_b(c.sb + B_FULL + 8 * sl, (it >> 2) & 1);
    bar_sync(c.myid, 256);
    wgmma_fence();
    issue_qk<true>(s, q, rt(desc_k(SM_RING + sl * SLOT)));
    wgmma_commit();
    bar_arrive(c.otherid, 256);
    wgmma_wait<0>();
    pin<72>(s); pin<32>(q);
    do_exp<64, 72, SAFE>(s, m0, m1);
    do_exp<0, 8, SAFE>(s, m0, m1);
    pin<8>(s);
#pragma unroll
    for (int i = 32; i < 36; i++) { p[i] = tail ? pack2(s[2 * i], s[2 * i + 1]) : 0u; asm volatile("" : "+r"(p[i])); }
    sched_fence();
    q_move<24>(q);
    const uint64_t dv = rt(desc_mn(SM_RING + sl * SLOT));
    float n0 = 0.f, n1 = 0.f;
#pragma unroll
    for (int k = 0; k < 8; k++) {
        if (k < 7) {
#pragma unroll
            for (int i = 8 * k + 8; i < 8 * k + 16; i++) { if constexpr (SAFE) s[i] -= (i & 2) ? m1 : m0; s[i] = ex2(s[i]); asm volatile("" : "+f"(s[i])); }
        }
#pragma unroll
        for (int i = 4 * k; i < 4 * k + 4; i++) { p[i] = pack2(s[2 * i], s[2 * i + 1]); asm volatile("" : "+r"(p[i])); }
        if (!SAFE && k < 4) {
            n0 += norm4(q, 8 * k); n1 += norm4(q, 8 * k + 1);
            asm volatile("" : "+f"(n0), "+f"(n1));
        }
        if (!SAFE && k == 4) {
            const uint32_t fl = c.flag | unsafe_norms(n0, n1);
            if (c.lane0) { sts32(c.sb + SM_FLAGS + (threadIdx.x >> 5) * 4, fl); mbar_arrive(c.sb + B_DEC); }
        }
        sched_fence();
        wgmma_fence();
        if (k == 0) wgmma_rs128_mn_i(o, p[32], p[33], p[34], p[35], dv + 2048);
        wgmma_rs128_mn(o, p[4 * k], p[4 * k + 1], p[4 * k + 2], p[4 * k + 3], dv + (uint64_t)(k * 256));
        wgmma_commit();
        sched_fence();
    }
    mbar_wait(c.sb + B_FULL + 8 * ns, ((it + 1) >> 2) & 1);
    bar_sync(c.myid, 256);
    wgmma_fence();
    issue_qk<false>(s, q, rt(desc_k(SM_RING + ns * SLOT)));
    wgmma_commit();
    bar_arrive(c.otherid, 256);
    wgmma_wait<0>();
    pin<64>(s); pin<64>(o); pin<36>(p);
    if (c.lane0) mbar_arrive(c.sb + B_EMPTY + 8 * sl);
    do_exp<0, 64, SAFE>(s, m0, m1);
    do_pack<64>(s, p, true);
}

template <bool SAFE>
__device__ __forceinline__ bool attention(const Cons& c, int it, uint32_t (&q)[32], float mA0, float mA1, float mB0, float mB1,
                                          uint8_t* __restrict__ out) {
    float s[72], o[64];
    uint32_t p[36];
    float m0 = mA0, m1 = mA1;
    first_steps<SAFE>(c, it, s, o, p, q, m0, m1, blockIdx.x - 11 * ((blockIdx.x * 373) >> 12) >= 2);
    it += 2;
    if (!SAFE) {
        mbar_wait_cl(c.sb + B_DEC, 0);
        cluster_arrive_relaxed();
        if (__builtin_expect(uni(read_flags(c.sb)), 0)) return false;
    }
#pragma unroll 1
    for (int seg = 0; seg < 2; seg++) {
        const int end = it + (seg ? 38 - c.myid : 5);
#pragma unroll 1
        for (; it < end; it++) step<0, SAFE>(c, it, s, o, p, q, m0, m1, true);
        if (seg == 0) {
            cluster_wait();
            mbar_wait_cl(c.sb + B_QB, 0);
            m0 = mB0; m1 = mB1;
            step<2, SAFE>(c, it, s, o, p, q, m0, m1, blockIdx.x & 1);
            step<3, SAFE>(c, it + 1, s, o, p, q, m0, m1, true);
            it += 2;
        }
    }
    DERIVE
    const int tid128 = tid & 127;
    const uint64_t dvl = desc_mn(SM_RING + ((it + 3) & 3) * SLOT);
    if (c.myid == 1) {
        float y[16];
        uint32_t xa[4];
        uint32_t wa[64], wb[64];
        const uint32_t wo = sb + SM_RING + (8 * hi + (lane & 7)) * 128 + (((2 * warp + ((lane >> 3) & 1)) ^ (lane & 7)) << 4);
        auto load_wt = [&](uint32_t (&w)[64], int m, int k) {
            asm volatile("ldmatrix.sync.aligned.m8n8.x4.trans.shared.b16 {%0,%1,%2,%3}, [%4];"
                         : "=r"(w[4 * k]), "=r"(w[4 * k + 1]), "=r"(w[4 * k + 2]), "=r"(w[4 * k + 3]) : "r"(wo + ((it + m) & 3) * SLOT + k * 2048) : "memory");
        };
        auto slab_gemm = [&](uint32_t (&w)[64], int m) {
            const uint64_t db = rt(desc_k(SM_PARK + 16384 + m * 4096));
            pin<64>(w);
            wgmma_fence();
#pragma unroll
            for (int k = 0; k < 8; k++) {
                wgmma_rs16_k<0>(y, w[4 * k], w[4 * k + 1], w[4 * k + 2], w[4 * k + 3], db + koff(k));
                wgmma_rs16_k<8>(y, w[32 + 4 * k], w[33 + 4 * k], w[34 + 4 * k], w[35 + 4 * k], db + koff(k));
            }
            wgmma_commit();
        };
        bar_sync(c.myid, 256);
        pin<32>(p); pin<64>(o);
        wgmma_fence();
        issue_pv(o, p, dvl);
        wgmma_commit();
        bar_arrive(c.otherid, 256);
        mbar_wait(sb + B_RFREE, 0);
        {
#pragma unroll
            for (int j = 0; j < 4; j++)
                xa[j] = sb + SM_XS + swz((j >> 1) * 8 + 2 * t + (j & 1), 4 * (warp >> 1) + (gq >> 1)) + 8 * (warp & 1) + 2 * (gq & 1);
#pragma unroll
            for (int k = 0; k < 16; k++) {
                uint32_t v;
                asm volatile("ld.shared.u16 %0, [%1];" : "=r"(v) : "r"(xa[((k >> 2) & 1) * 2 + (k & 1)] + (k >> 3) * 1024 + (k & 2) * 2));
                y[k] = blo(v);
            }
            mbar_wait(sb + B_FULL + 8 * (it & 3), (it >> 2) & 1);
            pin<16>(y);
            sched_fence();
        }
        const uint32_t rdst = mapa(sb + SM_RX + tid128 * 16, rank ^ 1), rbar = mapa(sb + B_RECV, rank ^ 1);
        wgmma_wait<0>();
        pin<64>(o);
        {
            const float u0 = 0.5f * (o[0] + o[33]), u1 = 0.5f * (o[2] + o[35]);
            float s0 = 0.f, s1 = 0.f;
#pragma unroll
            for (int k = 0; k < 8; k++) {
                if (k) {
                    s0 += (o[8 * k - 8] + o[8 * k - 7]) + (o[8 * k - 4] + o[8 * k - 3]); s1 += (o[8 * k - 6] + o[8 * k - 5]) + (o[8 * k - 2] + o[8 * k - 1]);
                    asm volatile("" : "+f"(s0), "+f"(s1));
                }
                st_async4(rdst + k * 2048, pack2(o[8 * k] - u0, o[8 * k + 1] - u0), pack2(o[8 * k + 2] - u1, o[8 * k + 3] - u1),
                          pack2(o[8 * k + 4] - u0, o[8 * k + 5] - u0), pack2(o[8 * k + 6] - u1, o[8 * k + 7] - u1), rbar);
                load_wt(wa, 0, 2 * k); load_wt(wa, 0, 2 * k + 1);
                sched_fence();
            }
            s0 += (o[56] + o[57]) + (o[60] + o[61]); s1 += (o[58] + o[59]) + (o[62] + o[63]);
            st_async4(rdst + 16384, __float_as_uint(u0), __float_as_uint(u1), __float_as_uint(s0), __float_as_uint(s1), rbar);
        }
        if (b < NSLABX) {
            mbar_wait(sb + B_FULL + 8 * ((it + 1) & 3), ((it + 1) >> 2) & 1);
#pragma unroll
            for (int k = 0; k < 16; k++) load_wt(wb, 1, k);
            mbar_wait(sb + B_AGG, 0);
            pin<16>(y);
            slab_gemm(wa, 0);
            slab_gemm(wb, 1);
            wgmma_wait<0>();
            pin<16>(y);
#pragma unroll
            for (int k = 0; k < 16; k++)
                asm volatile("st.shared.u16 [%0], %1;" ::"r"(xa[((k >> 2) & 1) * 2 + (k & 1)] + (k >> 3) * 1024 + (k & 2) * 2), "h"(__bfloat16_as_ushort(__float2bfloat16(y[k]))) : "memory");
            bar_sync(8, 128);
            uint4* op = reinterpret_cast<uint4*>(out + (size_t)rowX * 256) + tid128;
            const uint32_t a = sb + SM_XS + swz(tid128 >> 4, l16);
            op[0] = lds128(a); op[128] = lds128(a + 2048);
        }
    } else {
        const int row = b * 64 + warp * 16 + gq;
        mbar_wait(sb + B_FULL + 8 * (it & 3), (it >> 2) & 1);
        bar_sync(c.myid, 256);
        wgmma_fence();
        issue_qk<false>(s, q, rt(desc_k(SM_RING + (it & 3) * SLOT)));
        wgmma_commit();
        bar_arrive(c.otherid, 256);
        const float cc = __uint_as_float(lds32(sb + SM_C));
        mbar_wait(sb + B_FULL + 8 * ((it + 1) & 3), ((it + 1) >> 2) & 1);
        mbar_wait(sb + B_AGG, 0);
        wgmma_wait<0>();
        pin<64>(s); pin<32>(q);
        do_exp<0, EXP3, SAFE>(s, m0, m1);
        pin<EXP3>(s);
#pragma unroll
        for (int i = 0; i < EXP3 / 2 - 4; i++) { q[i] = pack2(s[2 * i], s[2 * i + 1]); asm volatile("" : "+r"(q[i])); }
        sched_fence();
        bar_sync(c.myid, 256);
        pin<32>(p); pin<64>(o);
        wgmma_fence();
        issue_pv(o, p, dvl);
        wgmma_commit();
        sched_fence();
        do_exp<EXP3, 64, SAFE>(s, m0, m1);
#pragma unroll
        for (int i = EXP3 / 2 - 4; i < 32; i++) q[i] = pack2(s[2 * i], s[2 * i + 1]);
        pin<32>(q);
        sched_fence();
        wgmma_fence();
        {
            const uint64_t dv = desc_mn(SM_RING + (it & 3) * SLOT);
#pragma unroll
            for (int k = 0; k < 8; k++) wgmma_rs128_mn(o, q[4 * k], q[4 * k + 1], q[4 * k + 2], q[4 * k + 3], dv + (uint64_t)(k * 256));
        }
        wgmma_commit();
        it++;
        const uint64_t da = rt(desc_k(SM_PARK)), db = rt(desc_pn(SM_RING + (it & 3) * SLOT));
        it++;
        mbar_wait(sb + B_FULL + 8 * (it & 3), (it >> 2) & 1);
        wgmma_wait<0>();
        pin<64>(o); pin<32>(p); pin<32>(q);
        float s0, s1;
        row_sums(o, s0, s1);
        asm volatile("" : "+f"(s0), "+f"(s1)::"memory");
        uint4* op = reinterpret_cast<uint4*>(out + (size_t)row * 256) + t;
        const uint64_t dw = desc_pn(SM_RING + (it & 3) * SLOT);
        mbar_wait_cl(sb + B_RECV, 0);
        if (tid128 == 0) { mbar_arrive(sb + B_FIN); }
        {
            const uint4 e = lds128(sb + SM_RX + 16384 + tid128 * 16);
            uint4 r[8];
#pragma unroll
            for (int k = 0; k < 8; k++) r[k] = lds128(sb + SM_RX + tid128 * 16 + k * 2048);
            s0 = quad_sum(s0 + __uint_as_float(e.z)); s1 = quad_sum(s1 + __uint_as_float(e.w));
            const float k0 = safe_div(cc * 128.0f, s0), k1 = safe_div(cc * 128.0f, s1);
            const float c0 = fmaf(__uint_as_float(e.x), k0, -cc), c1 = fmaf(__uint_as_float(e.y), k1, -cc);
#pragma unroll
            for (int k = 0; k < 8; k++) {
#pragma unroll
                for (int j = 0; j < 4; j++) {
                    p[4 * k + j] = pack2(fmaf(o[8 * k + 2 * j] + blo(comp(r[k], j)), (j & 1) ? k1 : k0, (j & 1) ? c1 : c0),
                                         fmaf(o[8 * k + 2 * j + 1] + bhi(comp(r[k], j)), (j & 1) ? k1 : k0, (j & 1) ? c1 : c0));
                    asm volatile("" : "+r"(p[4 * k + j]));
                }
                if ((k + 1) % KG == 0) {
                    wgmma_fence();
#pragma unroll
                    for (int kk = 2 * (k + 1 - KG); kk < 8 && kk < 2 * (k + 1); kk++) {
                        if (kk) wgmma_ss128_mn(s, da + koff(kk), db + (uint64_t)(kk * 128)); else wgmma_ss128_mn_i(s, da, db);
                    }
#pragma unroll
                    for (int kk = k + 1 - KG; kk <= k; kk++) wgmma_rs128_mn(s, p[4 * kk], p[4 * kk + 1], p[4 * kk + 2], p[4 * kk + 3], dw + (uint64_t)(kk * 128));
                    wgmma_commit();
                    sched_fence();
                }
            }
        }
        uint4 xr[8];
#pragma unroll
        for (int i = 0; i < 8; i++) xr[i] = lds128(sb + SM_XR + (warp * 16 + gq) * 256 + t * 16 + (i >> 1) * 64 + (i & 1) * 2048);
        sched_fence();
        wgmma_wait<0>();
        pin<64>(s);
#pragma unroll
        for (int i = 0; i < 8; i++) {
            const int a = 16 * (i >> 1) + 2 * (i & 1);
            op[(i & 1) * 128 + 4 * (i >> 1)] = make_uint4(pack2(s[a] + blo(xr[i].x), s[a + 1] + bhi(xr[i].x)), pack2(s[a + 4] + blo(xr[i].y), s[a + 5] + bhi(xr[i].y)),
                                                          pack2(s[a + 8] + blo(xr[i].z), s[a + 9] + bhi(xr[i].z)), pack2(s[a + 12] + blo(xr[i].w), s[a + 13] + bhi(xr[i].w)));
            sched_fence();
        }
    }
    asm volatile("{\n.reg .pred p;\n.reg .u32 y;\nmov.u32 y, %ctaid.y;\nsetp.eq.u32 p, y, 0;\n@p exit;\n}" ::: "memory");
    return true;
}

__device__ __forceinline__ void store_partial(Scratch* sc, uint32_t sb, int b) {
    mbar_wait(sb + B_STAGED, 0);
    bulk_s2g(sc->part + (size_t)b * PART_BYTES, sb + SM_PARK, PART_BYTES);
    bulk_wait_all();
    red_release_u32(&sc->a[(b * 373) >> 12], 1);
}
__device__ __forceinline__ void load_w(uint32_t sb, const uint8_t* wq, const uint8_t* wk, int rank, int i) {
    const int part = i >> 6, j = i & 63;
    const uint8_t* p = (part == 2 ? wk + rank * 16384 : wq + part * 16384) + j * 16;
    const uint32_t d = sb + SM_WQ + part * 16384 + swz(j >> 4, j & 15);
#pragma unroll
    for (int g = 0; g < 8; g++) { cp16(d + g * 2048, p + g * 2048); cp16((d ^ 64) + 512 + g * 2048, p + g * 2048 + 1024); }
    cp_commit();
}

__global__ void __cluster_dims__(2, 1, 1) __launch_bounds__(384, 1)
gps_kernel(const uint8_t* __restrict__ x, const int* __restrict__ src, const int* __restrict__ dst, const __nv_bfloat16* __restrict__ deg_inv,
           const uint8_t* __restrict__ w_msg, const uint8_t* __restrict__ wq, const uint8_t* __restrict__ wk, const uint8_t* __restrict__ wv,
           const uint8_t* __restrict__ w_out, uint8_t* __restrict__ out, Scratch* const sc0, unsigned long long* const h0,
           unsigned long long* const h1) {
    extern __shared__ __align__(1024) uint8_t smem_raw[];
    const int wrp = uni(threadIdx.x >> 5);
    if (wrp >= 10 || (wrp >> 2) == ((blockIdx.x & 1) ^ 1))
        load_w(SB0 + ((blockIdx.x & 1) << 24), wq, wk, blockIdx.x & 1, wrp >= 10 ? threadIdx.x - 192 : threadIdx.x & 127);
    uint16_t seen = 0;
    if (__builtin_expect(wrp < 8, 1)) {
        uint32_t q[32];
        uint32_t flag = 0;
        {
        const int tid = threadIdx.x, b = blockIdx.x, lane = tid & 31, warp = wrp & 3, gq = lane >> 2, t = lane & 3, rank = b & 1;
        [[maybe_unused]] const int wg = wrp >> 2, tid128 = tid & 127;
        const uint32_t sb = SB0 + (rank << 24);
        const bool isR = wg == rank;
        const uint32_t off0 = gq * 128 + ((((gq & 1) * 4 + t) ^ gq) << 4), off1 = off0 ^ 64;
        const uint32_t gof0 = gq * 256 + ((gq & 1) * 4 + t) * 16, gof1 = gof0 ^ 64;
        const bool hasX = warp < 2 && b < NSLABX;
        auto load_group = [&](uint32_t d, int row) {
            const uint8_t* p = x + (size_t)row * 256;
            cp16(d + off0, p + gof0); cp16(d + off1, p + gof1); cp16(d + off0 + 1024, p + gof0 + 128); cp16(d + off1 + 1024, p + gof1 + 128);
            cp_commit();
        };
        const int rowA = ROWS_B + 128 * ((b * 373) >> 12) + 16 * wrp;
        if (isR) {
#pragma unroll 1
            for (int g = hasX ? 0 : 1; g < 5; g++) {
                load_group(sb + (g == 0 ? SM_XS + warp * 2048 : g < 3 ? SM_XA + wrp * 4096 + (g - 1) * 2048 : SM_XB + (2 * warp + g - 3) * 2048),
                           g == 0 ? ROWS_B + 16 * b + 8 * warp : g < 3 ? rowA + 8 * g - 8 : 64 * b + 16 * warp + 8 * g - 24);
            }
            bar_arrive(1, 256);
        }
        cluster_arrive_relaxed();
        asm volatile("setmaxnreg.inc.sync.aligned.u32 %0;" ::"n"(REGC));
        const uint32_t dq = sb + (isR ? SM_PARK : SM_RECV) + rank * 16384 + warp * 4096;
        auto send_q = [&]() {
            fence_async_smem();
            __syncwarp();
            if (lane == 0) {
                const uint32_t rbar = mapa(sb + (isR ? B_DEC : B_G), rank ^ 1);
                if (isR) asm volatile("st.async.shared::cluster.mbarrier::complete_tx::bytes.u32 [%0], %1, [%2];" ::"r"(mapa(sb + SM_FLAGS + 32 + warp * 4, rank ^ 1)), "r"(flag), "r"(rbar) : "memory");
                else { bulk_s2c(mapa(dq, rank ^ 1), dq, 4096, rbar); mbar_arrive(sb + B_G); }
            }
            __syncwarp();
        };
        const bool isQ = b == NSLABX - 1;
        auto gemm = [&](float (&acc)[64], uint64_t da, uint64_t db) {
            wgmma_fence();
            wgmma_ss128_k_i(acc, da, db);
#pragma unroll
            for (int k = 1; k < 8; k++) wgmma_ss128_k(acc, da + koff(k), db + koff(k));
            wgmma_commit();
        };
        auto finish = [&](float (&acc)[64], int rs_row, bool wait_rs) {
            float m0, m1;
            row_sums(acc, m0, m1);
            m0 = quad_sum(m0) * (1.0f / 128.0f); m1 = quad_sum(m1) * (1.0f / 128.0f);
            if (wait_rs) mbar_wait(sb + B_RS, 0);
            const uint32_t ra = sb + SM_RS + (rs_row + 16 * warp + gq) * 4;
            const float k0 = rs_row < 0 ? 1.0f : __uint_as_float(lds32(ra)) * QSCALE, k1 = rs_row < 0 ? 1.0f : __uint_as_float(lds32(ra + 32)) * QSCALE;
            const float qd = rs_row < 0 ? 0.f : PSHIFT / (128.0f * KV_A * KV_C0);
            m0 = fmaf(m0, -k0, qd); m1 = fmaf(m1, -k1, qd);
#pragma unroll
            for (int i = 0; i < 64; i += 4) {
                q[i / 2] = pack2(fmaf(acc[i], k0, m0), fmaf(acc[i + 1], k0, m0));
                q[i / 2 + 1] = pack2(fmaf(acc[i + 2], k1, m1), fmaf(acc[i + 3], k1, m1));
            }
        };
        uint32_t qa[4];
#pragma unroll
        for (int k = 0; k < 4; k++) { qa[k] = dq + swz(lane & 15, 2 * k + (lane >> 4)); asm volatile("" : "+r"(qa[k])); }
        auto store_q = [&]() {
#pragma unroll
            for (int k = 0; k < 8; k++) stsm4(qa[k & 3] + (k >> 2) * 1024, q[4 * k], q[4 * k + 1], q[4 * k + 2], q[4 * k + 3]);
        };
        sched_fence();
#pragma unroll 1
        for (int g = isR ? !hasX : 3; g < 3; g++) {
            if (g == 0) cp_wait<4>(); else if (g == 1) cp_wait<1>(); else cp_wait<0>();
            const int u = g ? 2 * warp + g - 1 : 8 + warp;
            const uint32_t raw = sb + (g ? SM_XB : SM_XS - 8 * 2048) + u * 2048;
            const uint4 v[4] = {lds128(raw + off0), lds128(raw + off1), lds128(raw + off0 + 1024), lds128(raw + off1 + 1024)};
            float f[32], a[4] = {0.f, 0.f, 0.f, 0.f};
#pragma unroll
            for (int i = 0; i < 16; i++) { const uint32_t e = comp(v[i >> 2], i & 3); f[2 * i] = blo(e); f[2 * i + 1] = bhi(e); a[(2 * i) & 3] += f[2 * i]; a[(2 * i + 1) & 3] += f[2 * i + 1]; }
            const float mean = quad_sum((a[0] + a[1]) + (a[2] + a[3])) * (1.0f / 128.0f);
            a[0] = a[1] = a[2] = a[3] = 0.f;
#pragma unroll
            for (int i = 0; i < 32; i++) { f[i] -= mean; a[i & 3] = fmaf(f[i], f[i], a[i & 3]); }
            const float var = quad_sum((a[0] + a[1]) + (a[2] + a[3])) * (1.0f / 128.0f);
            const float rs = rsqrtf(var + 1e-5f);
            const float ka = KV_A * rs, kb = KV_A * KV_C0;
            uint8_t* d = sc0->kv + (g ? 528 * g - 528 + 4 * b + warp : 1056 + 2 * b + warp) * 2048;
#pragma unroll
            for (int i = 0; i < 4; i++)
                *reinterpret_cast<uint4*>(d + ((i & 1) ? off1 : off0) + (i >> 1) * 1024) =
                    make_uint4(pack2(fmaf(f[8 * i], ka, kb), fmaf(f[8 * i + 1], ka, kb)), pack2(fmaf(f[8 * i + 2], ka, kb), fmaf(f[8 * i + 3], ka, kb)),
                               pack2(fmaf(f[8 * i + 4], ka, kb), fmaf(f[8 * i + 5], ka, kb)), pack2(fmaf(f[8 * i + 6], ka, kb), fmaf(f[8 * i + 7], ka, kb)));
            if (t == 0 && g == 0) sc0->rsx[16 * b + 8 * warp + gq] = rs;
            if (t < 2) sts32(sb + (t ? SM_MEAN : SM_RS + 512) + (u * 8 + gq) * 4, __float_as_uint(t ? mean : rs));
            float r2 = var * rs * rs;
            r2 += __shfl_xor_sync(~0u, r2, 4); r2 += __shfl_xor_sync(~0u, r2, 8); r2 += __shfl_xor_sync(~0u, r2, 16);
            if (lane == 0) sts32(sb + SM_R2 + u * 4, __float_as_uint(r2));
            bar_arrive(g ? 13 + g : 6, g ? 160 : 96);
        }
        if (isR) cluster_wait(); else cp_wait<0>();
        fence_async_smem();
        bar_sync(isR ? 7 : 3, isR ? 128 : 192);
        if (isR && isQ) bar_arrive(4, 256);
        const uint64_t dg = rt(desc_k(SM_RECV)), dxa = rt(desc_k(SM_XA + wg * 16384));
        float s[64], o[64];
        if (isR) mbar_wait_cl(sb + B_G, 0);
        gemm(o, rt(desc_k(isR ? SM_XB : SM_WK)), rt(desc_k(isR ? SM_RECV : SM_WQ)));
        if (isR) { gemm(s, dxa, dg); wgmma_wait<1>(); }
        else { load_group(sb + SM_XA + wrp * 4096, rowA); load_group(sb + SM_XA + wrp * 4096 + 2048, rowA + 8); cluster_wait(); wgmma_wait<0>(); }
        pin<64>(o);
        finish(o, isR ? 128 : -1, false);
        store_q();
        if (isR) flag = unsafe_rows(q) ? 2 : 0; else cp_wait<0>();
        send_q();
        if (!isR) {
            mbar_wait_cl(sb + B_G, 0);
            if (isQ) {
                bar_sync(4, 256);
                float y[16];
                const uint64_t dx = rt(desc_k(SM_XS));
                wgmma_fence();
                wgmma_ss16_k_i<0>(y, dg, dx); wgmma_ss16_k_i<8>(y, dg + 1024, dx);
#pragma unroll
                for (int k = 1; k < 8; k++) { wgmma_ss16_k<0>(y, dg + koff(k), dx + koff(k)); wgmma_ss16_k<8>(y, dg + 1024 + koff(k), dx + koff(k)); }
                wgmma_commit();
                const float2 pa = lds64f(sb + SM_RS + 768 + 8 * t), pb = lds64f(sb + SM_RS + 800 + 8 * t);
                const float a0 = pa.x * QSCALE, a1 = pa.y * QSCALE, b0 = pb.x * QSCALE, b1 = pb.y * QSCALE;
                const uint32_t d = sb + SM_XS + 4096 + swz(8 * (lane >> 4) + (lane & 7), 2 * warp + ((lane >> 3) & 1));
                wgmma_wait<0>();
                pin<16>(y);
#pragma unroll
                for (int i = 0; i < 16; i += 8)
                    stsm4t(d + i * 128, pack2(y[i] * a0, y[i + 1] * a1), pack2(y[i + 2] * a0, y[i + 3] * a1), pack2(y[i + 4] * b0, y[i + 5] * b1), pack2(y[i + 6] * b0, y[i + 7] * b1));
                fence_async_smem();
            }
            gemm(s, dxa, dg);
        }
        wgmma_wait<0>();
        pin<64>(s);
        if (lane == 0) mbar_arrive(sb + B_XD);
        finish(s, 64 * wg, true);
        }
        Cons c;
        {
            DERIVE
            c.sb = sb; c.lane0 = lane == 0; c.myid = (wrp >> 2) == rank ? 2 : 1; c.otherid = 3 - c.myid;
            c.flag = flag;
        }

        if (__builtin_expect(!attention<false>(c, 0, q, 0.f, 0.f, 0.f, 0.f, out), 0)) {
            DERIVE
            const uint32_t fl = read_flags(sb);
            q_move<24>(q);
            for (int it = 1; it < 4; it++) {
                mbar_wait(sb + B_FULL + 8 * it, 0);
                if (lane == 0) mbar_arrive(sb + B_EMPTY + 8 * it);
            }
            mbar_wait_cl(sb + B_QB, 0);
            float mA0 = -INFINITY, mA1 = -INFINITY, mB0 = -INFINITY, mB1 = -INFINITY;
#pragma unroll 1
            for (int it = 4; it < 4 + 79; it++) {
                float s[64], o[64];
                mbar_wait(sb + B_FULL + 8 * (it & 3), (it >> 2) & 1);
                wgmma_fence();
                issue_qk<false>(s, q, desc_k(SM_RING + (it & 3) * SLOT));
                {
                    const uint64_t da = desc_k(SM_PARK + (__shfl_sync(~0u, tid, 0) >> 7) * 16384), db = desc_k(SM_RING + (it & 3) * SLOT);
                    wgmma_ss128_k_i(o, da, db);
#pragma unroll
                    for (int k = 1; k < 8; k++) wgmma_ss128_k(o, da + koff(k), db + koff(k));
                }
                wgmma_commit();
                wgmma_wait<0>();
                pin<64>(s); pin<64>(o);
                if (lane == 0) mbar_arrive(sb + B_EMPTY + 8 * (it & 3));
#pragma unroll
                for (int i = 0; i < 64; i += 4) {
                    mA0 = fmaxf(mA0, fmaxf(s[i], s[i + 1])); mA1 = fmaxf(mA1, fmaxf(s[i + 2], s[i + 3]));
                    mB0 = fmaxf(mB0, fmaxf(o[i], o[i + 1])); mB1 = fmaxf(mB1, fmaxf(o[i + 2], o[i + 3]));
                }
            }
            mA0 = quad_max(mA0); mA1 = quad_max(mA1); mB0 = quad_max(mB0); mB1 = quad_max(mB1);
            if (!(fl & 1)) { mA0 = 0.f; mA1 = 0.f; }
            if (!(fl & 2)) { mB0 = 0.f; mB1 = 0.f; }
            attention<true>(c, 4 + 79, q, mA0, mA1, mB0, mB1, out);
        }
        if (blockIdx.y == 0) return;
        asm volatile("setmaxnreg.dec.sync.aligned.u32 %0;" ::"n"(REGB));
    } else {
        asm volatile("setmaxnreg.dec.sync.aligned.u32 %0;" ::"n"(REGB));
        { DERIVE_SC
        if (tid == 256) {
            if ((uint32_t)__cvta_generic_to_shared(smem_raw) != sb) asm volatile("trap;");
#pragma unroll
            for (int i = 0; i < 20; i++) mbar_init(sb + SM_BAR + 8 * i, i < 13 ? (0x318a588881111ull >> (4 * i)) & 15 : i == 18 ? 8 : 1);
            mbar_expect_tx(sb + B_G, 16384); mbar_expect_tx(sb + B_DEC, 16); mbar_init(sb + B_QB, 1); mbar_expect_tx(sb + B_QB, 16384); mbar_expect_tx(sb + B_RECV, 18432);
            mbar_expect_tx(sb + B_RS, 512); mbar_expect_tx(sb + B_FULL, 36864); mbar_expect_tx(sb + B_FULL + 8, 32768);
            mbar_expect_tx(sb + B_FULL + 16, 32768); mbar_expect_tx(sb + B_FULL + 24, 32768);
            asm volatile("fence.mbarrier_init.release.cluster;" ::: "memory");
        }
        __syncwarp();
        cluster_arrive_relaxed();
        if (wrp == 8) {
            const int tA = (b * 373) >> 12, sA = b - 11 * tA;
            if (lane == 0) asm volatile("ld.relaxed.gpu.global.u16 %0, [%1];" : "=h"(seen) : "l"(h0) : "memory");
            if (lane < 2) {
                const void* p = lane ? (const void*)(sc->kv + (sA < 2 ? 528 + 8 * sA : 526 + 9 * sA) * 4096) : (const void*)(sc->rsx + 128 * tA);
                poll_cnt(h1 + 16 * (lane ? 12 + sA : tA), 8 + lane);
                bulk_g2s(sb + (lane ? SM_RING : SM_RS), p, lane ? 36864 : 512, sb + (lane ? B_FULL : B_RS));
            }
            rejoin();
            bar_arrive(8, 96);
            cluster_wait();
            cluster_arrive_relaxed();
        } else {
            if (wrp >= 10) { cp_wait<0>(); fence_async_smem(); bar_arrive(3, 192); }
            cluster_wait();
            if (wrp != 11) cluster_arrive_relaxed();
            if (wrp >= 10) bar_sync(8, 96);
            if (wrp != 9 || b < NSLABX) {
                unsigned long long* pub = warp == 3 ? h0 : h1 + 16 * (warp == 2 ? 23 + (b >> 2) : lane == 1 ? (isQ ? 63 : b >> 3) : 12 - (lane >> 1) + (b < 16 ? b >> 3 : ((b + 2) * 57) >> 9));
                bar_sync(warp == 1 ? 6 : 12 + warp, warp == 1 ? 96 : 160);
                unsigned long long inc = 1;
                if (wrp == 11) {
                    const float r2 = half_sum(lane < (b < NSLABX ? 10 : 8) ? __uint_as_float(lds32(sb + SM_R2 + 4 * lane)) : 0.f);
                    inc |= (unsigned long long)(fminf(r2, 81.0f) * 4294967296.0f) << 16;
                }
                if (lane < (warp != 1 ? 1 : b == 8 || b == 16 ? 3 : 2)) {
                    asm volatile("red.release.gpu.global.add.u64 [%0], %1;" ::"l"(pub), "l"(inc) : "memory");
                }
                __syncwarp();
            }
            if (wrp == 9) {
                int tau = b - 11 * ((b * 373) >> 12);
#pragma unroll 1
                for (int k = 1; k < 4; k++, tau += 11) {
                    if (lane == 0) {
                        mbar_wait(sb + (k == 1 ? B_G : B_XD), 0);
                        poll_cnt(h1 + 16 * (23 + tau), 4);
                        bulk_g2s(sb + SM_RING + k * SLOT, sc->kv + tau * 32768, 32768, sb + B_FULL + 8 * k);
                    }
                }
            }
        } }
    }
    {
        if (threadIdx.x == 256) {
            DERIVE
            if (seen < NCTA) poll_cnt(h0, NCTA);
            unsigned long long v;
            asm volatile("ld.acquire.gpu.global.u64 %0, [%1];" : "=l"(v) : "l"(h0) : "memory");
            fence_async_global();
            const bool redo = (v >> 48) < NN / 4;
            float root;
            asm("sqrt.approx.f32 %0, %1;" : "=f"(root) : "f"((float)(v >> 16) * (1.0f / (4294967296.0f * NN))));
            sts32(sb + SM_C, __float_as_uint(redo ? KV_C0 * fmaxf(root, 3.8e-6f) : KV_C0));
            sts32(sb + SM_FLAGS + 48, redo ? 4 : 0);
            mbar_arrive(sb + B_DEC);
            mbar_wait_b(sb + B_DEC, 0);
            asm volatile("fence.acquire.sync_restrict::shared::cluster.cluster;" ::: "memory");
            const bool fb = read_flags(sb);
            sts128(sb + SM_PST, fb ? 0 : 4, 4, fb ? 79 : 0, redo);
        }
        rejoin();
        if (uni(threadIdx.x >> 5) != 8) {
            DERIVE
            mbar_wait(sb + B_DEC, 0);
            if (uni(warp) == 3) {
                const uint32_t a = sb + SM_PARK + rank * 16384;
                if (lane == 0) bulk_s2c(mapa(a, rank ^ 1), a, 16384, mapa(sb + B_QB, rank ^ 1));
                mbar_wait(sb + B_QB, 0);
                cluster_arrive_relaxed();
            }
        }
        int st = 1;
#pragma unroll 1
        for (;; st ^= 16) {
            const int wrp = uni(threadIdx.x >> 5);
            if (wrp == 8) {
                DERIVE_SC
                if (lane == 0) {
                    const uint4 ps = lds128(sb + SM_PST);
                    int pj = ps.x, pidx = ps.y, pnpre = ps.z, hold = ps.w;
                    const int sA = b - 11 * ((b * 373) >> 12);
                    bool fresh = false, last = false;
#pragma unroll 1
                    for (int spin = 0;; spin++) {
                        if (fresh && !last && mbar_test(sb + B_REQ, st >> 4)) { if (lds32(sb + SM_CMD) != CMD_DONE) break; last = true; }
                        if (last && pj == 48) break;
                        if (hold) {
                            unsigned v;
                            asm volatile("ld.acquire.gpu.global.u32 %0, [%1];" : "=r"(v) : "l"(hold == 1 ? &sc->b : &sc->cw) : "memory");
                            if (v >= (hold == 1 ? NCTA : 4)) { fence_async_global(); if (hold == 2) mbar_arrive(sb + B_W2); hold = 0; }
                        }
                        const int sl = pidx & 3;
                        if (pj < 48 && !hold && mbar_try(sb + B_EMPTY + 8 * sl, ((pidx >> 2) & 1) ^ 1, PWAIT)) {
                            const uint8_t* p;
                            uint32_t bytes = 32768;
                            if (pnpre) {
                                pnpre--;
                                p = sc->kv + min(pnpre * 128, NN - 128) * 256;
                            } else if (pj < 46) {
                                p = sc->kv + (pj == 0 ? (sA < 2 ? 528 + 8 * sA : 526 + 9 * sA) : pj < 7 ? 88 * pj - 88 + 8 * sA : pj == 7 ? rank * 312 : rank * 313 + 8 * pj - 56) * 4096;
                                if (pj == 0 || pj == 7) bytes = 36864;
                                if (++pj == 38) hold = 2;
                            } else {
                                p = sc->w2p + (pj - 46) * 32768;
                                pj++;
                            }
                            mbar_expect_tx(sb + B_FULL + 8 * sl, bytes);
                            bulk_g2s(sb + SM_RING + sl * SLOT, p, bytes, sb + B_FULL + 8 * sl);
                            pidx++;
                            fresh = !mbar_test(sb + B_EMPTY + 8 * (pidx & 3), ((pidx >> 2) & 1) ^ 1);
                        } else {
                            fresh = pj >= 46 || hold;
                            if (pj >= 48 || hold) __nanosleep(PWAIT);
                            if (spin > 40000000) asm volatile("trap;");
                        }
                    }
                    sts128(sb + SM_PST, pj, pidx, pnpre, hold);
                }
                __syncwarp();
            } else {
                int cmd = -1;
                if ((st & 15) == 1) {
                    DERIVE_SC
                    const float cc = __uint_as_float(lds32(sb + SM_C));
                    const int bs = b - (b > 96), ne = isQ ? 0 : min(EPC, EE - bs * EPC);
                    if (bt < 4) {
                        if (bt == 0) mbar_expect_tx(sb + B_LD, (b < NSLABX ? 20480 : 16384) + 8 * ne);
                        const uint32_t bytes = bt == 0 ? 16384 : bt == 1 ? (b < NSLABX ? 4096 : 0) : 4 * ne;
                        const void* p = bt < 2 ? (const void*)(x + (bt ? rowX * 256 : b * 16384)) : (const void*)((bt == 2 ? src : dst) + bs * EPC);
                        if (bytes) bulk_g2s(sb + SM_RECV + (bt < 2 ? bt * 16384 : 10240 + bt * 5120), p, bytes, sb + B_LD);
                    }
                    if (isQ) {
                        rejoin();
#pragma unroll 1
                        for (int i = bt; i < NLC * 512; i += 96) reinterpret_cast<uint4*>(sc->Lacc)[i] = make_uint4(0, 0, 0, 0);
                        if (bt < 16) { sc->Lmax[bt] = 0u; reinterpret_cast<uint4*>(sc->h16)[bt] = make_uint4(0, 0, 0, 0); }
                        rejoin();
                        uint32_t bad = 0;
#pragma unroll 1
                        for (int n0 = 2 * wrp - 18; n0 < 16; n0 += 6) {
                            const uint4 v = lds128(sb + SM_XS + 4096 + swz(n0 + hi, l16));
                            float s1 = 0.f, s2 = 0.f;
#pragma unroll
                            for (int j = 0; j < 4; j++) { const float lo = blo(comp(v, j)), up = bhi(comp(v, j)); s1 += lo + up; s2 = fmaf(lo, lo, fmaf(up, up, s2)); }
                            sts32(sb + SM_XS + 8192 + (n0 + hi) * 4, __float_as_uint(half_sum(s1) * (KV_A * cc)));
                            bad |= !(half_sum(s2) <= NORM2_MAX);
                        }
                        fence_async_smem();
                        asm volatile("{\n.reg .pred p, q;\nsetp.ne.u32 p, %0, 0;\nbar.red.or.pred q, 5, 96, p;\nselp.u32 %0, 8, 0, q;\n}" : "+r"(bad)::"memory");
                        if (bt == 64) { bulk_s2g(sc->qL, sb + SM_XS + 4096, 4096 + 64); bulk_wait_all(); red_release_u32(&sc->ql, 1 + bad); }
                    }
                    mbar_wait(sb + B_LD, 0);
                    rejoin();
                    const bool redo = uni(lds32(sb + SM_FLAGS + 48));
                    const float hs = __fdividef(0.25f * KV_C0, cc);
#pragma unroll 1
                    for (int l0 = 2 * wrp - 18; l0 < (b < NSLABX ? 80 : 64); l0 += 6) {
                        const int lr = l0 + hi;
                        const uint4 v = lds128(sb + SM_RECV + lr * 256 + l16 * 16);
                        const float rs = __uint_as_float(lds32(sb + SM_RS + (128 + lr) * 4)) * hs, mr = -rs * __uint_as_float(lds32(sb + SM_MEAN + lr * 4));
                        const int row = lr < 64 ? b * 64 + lr : rowX + lr - 64;
                        float f[8];
#pragma unroll
                        for (int j = 0; j < 4; j++) { f[2 * j] = fmaf(blo(comp(v, j)), rs, mr); f[2 * j + 1] = fmaf(bhi(comp(v, j)), rs, mr); }
                        __half2 h[4];
#pragma unroll
                        for (int j = 0; j < 4; j++) h[j] = __floats2half2_rn(f[2 * j], f[2 * j + 1]);
                        *reinterpret_cast<uint4*>(sc->h16 + (row + 1) * 256 + l16 * 16) = *reinterpret_cast<const uint4*>(h);
                        if (redo) {
                            const float kb = KV_A * cc, ka = kb * (4.0f / KV_C0);
                            *reinterpret_cast<uint4*>(sc->kv + swz(lr < 64 ? (lr & 8) * 528 + 32 * b + (lr >> 4) * 8 + (lr & 7) : row, l16)) =
                                make_uint4(pack2(fmaf(f[0], ka, kb), fmaf(f[1], ka, kb)), pack2(fmaf(f[2], ka, kb), fmaf(f[3], ka, kb)),
                                           pack2(fmaf(f[4], ka, kb), fmaf(f[5], ka, kb)), pack2(fmaf(f[6], ka, kb), fmaf(f[7], ka, kb)));
                        }
                    }
                    if (!isQ) {
                        bar_sync(5, 96);
#pragma unroll 1
                        for (int i = bt; i < 1056 + 33; i += 96) sts128(sb + SM_RECV + i * 16, 0, 0, 0, 0);
                        bar_sync(5, 96);
#pragma unroll 1
                        for (int i = bt; i < ne / 4; i += 96) {
                            const uint4 s4 = lds128(sb + SM_RECV + 20480 + i * 16), d4 = lds128(sb + SM_RECV + 25600 + i * 16);
                            uint32_t bin[4], pos[4];
#pragma unroll
                            for (int k = 0; k < 4; k++) {
                                const uint32_t dv = comp(d4, k);
                                bin[k] = dv < ROWS_B ? dv >> 6 : (dv - ROWS_B) >> 4;
                                pos[k] = atoms_inc(sb + SM_RECV + 16896 + bin[k] * 4);
                            }
#pragma unroll
                            for (int k = 0; k < 4; k++) {
                                const uint32_t dv = comp(d4, k), e = (dv < ROWS_B ? dv & 63 : 64 + (dv & 15)) << 16 | (comp(s4, k) + 1);
                                if (pos[k] < 32) sts32(sb + SM_RECV + bin[k] * 128 + pos[k] * 4, e);
                                else {
                                    uint32_t o;
                                    asm volatile("atom.global.add.u32 %0, [%1], 1;" : "=r"(o) : "l"(&sc->ovf) : "memory");
                                    sc->ovfl[o] = make_int2(bin[k], e);
                                }
                            }
                        }
                        bar_sync(5, 96);
                        uint8_t* po = sc->inbox + (bt >> 3) * INBOX + bs * 128 + (((bt ^ bs) & 7) << 4);
#pragma unroll 1
                        for (int i = 0; i < 11; i++, po += 12 * INBOX) *reinterpret_cast<uint4*>(po) = lds128(sb + SM_RECV + (bt + 96 * i) * 16);
                    }
                    bar_sync(5, 96);
                    if (bt == 32) { red_release_u32(&sc->b, 1); }
                    const uint32_t qt = sb + (b < NSLABX ? SM_RECV + 16384 : SM_XS);
                    if (bt >= 64 && bt < 67 && !isQ && !isW) {
                        if (redo) poll_ge(&sc->b, NCTA);
                        poll_ge(&sc->ql, 1);
                        fence_async_global();
                        const uint32_t kb = b < NSLABX || b == 127 ? 16384 : 32768;
                        if (lane == 0) { sts32(sb + SM_BST + 4, __ldcg(&sc->ql) & 8); mbar_expect_tx(sb + B_LD, kb + 4096 + 64); }
                        bulk_g2s(lane == 0 ? sb + SM_RECV : lane == 1 ? qt : sb + SM_SH,
                                 lane ? sc->qL + (lane - 1) * 4096 : sc->kv + min((b < NSLABX ? b : 2 * b - 98) * 64, NN - 64) * 256, lane == 0 ? kb : lane == 1 ? 4096 : 64, sb + B_LD);
                    }
                    if (bt == 0 && b >= NSLABX) store_partial(sc, sb, b);
                    rejoin();
                    if (isQ) st += 3;
                    else if (isW) {
                        bar_sync(5, 96);
                        const uint8_t* wm = ((b >> 1) & 1 ? wv : w_msg) + rank * 16384;
#pragma unroll 1
                        for (int r = bt >> 4; r < 192; r += 6)
                            cp16(sb + (r < 128 ? SM_RECV : SM_PARK - 32768) + swz(r, l16), (r < 128 ? w_out : wm - 32768) + r * 256 + l16 * 16);
                        cp_commit(); cp_wait<0>();
                        st += 1; cmd = CMD_W0;
                    } else {
                        mbar_wait(sb + B_LD, 1);
                        rejoin();
                        const bool bad = uni(lds32(sb + SM_BST + 4));
                        st += bad ? 1 : 2; cmd = bad ? CMD_M : CMD_L;
                    }
                }
                if (cmd < 0 && (st & 14) == 2) {
                    DERIVE_SC
                    const bool second = st & 1;
                    if (isW) {
#pragma unroll 1
                        for (int n0 = 2 * wrp - 18; n0 < 32; n0 += 6) {
                            const int n = n0 + hi;
                            const uint32_t ap = sb + SM_XS + n * 256 + (l16 >> 2) * 64 + (l16 & 3) * 4;
                            const int d = rank * 64 + second * 32 + n;
                            const int go = ((b >> 1) & 1) * 32768 + (l16 >> 3) * 16384 + d * 128 + (((l16 & 7) ^ (d & 7)) << 4);
                            *reinterpret_cast<uint4*>(sc->w2p + go) = make_uint4(lds32(ap), lds32(ap + 16), lds32(ap + 32), lds32(ap + 48));
                        }
                        if (second) bar_sync(5, 96); else cmd = CMD_W1;
                    }
                    if (bt == 0 && second && !isW) {
                        fence_async_global();
#pragma unroll 1
                        for (int k = b >= NSLABX && b < 127; k >= 0; k--)
                            asm volatile("cp.reduce.async.bulk.global.shared::cta.bulk_group.add.f32 [%0], [%1], 8192;" ::"l"(sc->Lacc + (b & (NLC - 1)) * 2048), "r"(sb + (b < NSLABX ? SM_XS + 4096 : SM_PARK + k * 8192)) : "memory");
                        bulk_wait_all();
                    }
                    if (bt == 0 && (second || !isW)) { red_release_u32(isW ? &sc->cw : second ? &sc->l2 : &sc->l1, 1); }
                    if (!isW && !second) {
                        if (bt == 0) poll_ge(&sc->l1, NLT);
                        __syncwarp();
                        if (bt < 16) {
                            const uint32_t uu = __ldcg(&sc->Lmax[bt]);
                            sts32(sb + SM_SH + bt * 4, (uu & 0x80000000u) ? (uu & 0x7fffffffu) : ~uu);
                        }
                        cmd = CMD_L;
                    }
                    __syncwarp();
                    st++;
                }
                if (cmd < 0 && (st & 15) == 4) {
                    { DERIVE_SC
                    sts32(sb + SM_BST, st);
                    if (bt >= 32 && bt < (b < NSLABX ? 35 : 34)) {
                        poll_ge(&sc->b, NCTA);
                        fence_async_global();
                        if (lane == 0) mbar_expect_tx(sb + B_LD, INBOX + (b < NSLABX ? 160 : 128));
                        bulk_g2s(sb + SM_RECV + (lane ? 11136 + lane * 128 : 12288), lane ? (const void*)(deg_inv + (lane == 1 ? b * 64 : rowX)) : (const void*)(sc->inbox + b * INBOX),
                                 lane == 0 ? INBOX : lane == 1 ? 128 : 32, sb + B_LD);
                    }
                    if (bt == 64 && b < NSLABX) store_partial(sc, sb, b);
                    rejoin();
#pragma unroll 1
                    for (int i = bt; i < 656; i += 96) sts128(sb + SM_RECV + i * 16, 0, 0, 0, 0);
                    mbar_wait(sb + B_LD, isQ || isW);
                    bar_sync(5, 96);
                    auto place = [&](uint32_t e, uint32_t pos) {
                        if (pos < CAP) asm volatile("st.shared.u16 [%0], %1;" ::"r"(sb + SM_RECV + (e >> 16) * 128 + pos * 2), "h"((uint16_t)e) : "memory");
                    };
#pragma unroll 1
                    for (int i = wrp - 9; i < 20; i += 3) {
                        const int ln = (i >> 2) * 32 + lane;
                        uint4 v = make_uint4(0, 0, 0, 0), v2 = v;
                        if (ln < 131) { const uint32_t a = sb + SM_RECV + 12288 + ln * 128 + ((((i & 3) ^ ln) & 7) << 4); v = lds128(a); v2 = lds128(a ^ 64); }
#pragma unroll 1
                        while (__any_sync(~0u, v.x)) {
                            uint32_t pos[4];
#pragma unroll
                            for (int k = 0; k < 4; k++) pos[k] = atoms_inc_if(sb + SM_RECV + (comp(v, k) >> 16) * 128 + 124, comp(v, k));
#pragma unroll
                            for (int k = 0; k < 4; k++) place(comp(v, k), pos[k]);
                            v = v2; v2.x = 0;
                        }
                    }
                    const int no = uni(__ldcg(&sc->ovf));
#pragma unroll 1
                    for (int i = bt; i < no; i += 96) { const int2 e2 = __ldcg(&sc->ovfl[i]); if (e2.x == b) place(e2.y, atoms_inc(sb + SM_RECV + (e2.y >> 16) * 128 + 124)); }
                    }
                    { DERIVE_SC
                    bar_sync(5, 96);
                    const bool ov = __any_sync(~0u, max(max(lds32(sb + SM_RECV + lane * 128 + 124), lds32(sb + SM_RECV + 4096 + lane * 128 + 124)), lds32(sb + SM_RECV + 8192 + l16 * 128 + 124)) > CAP);
                    sts32(sb + SM_BST + 8, ov);
                    if (bt == 32 && !ov) bulk_g2s(sb + SM_XR, x + b * 16384, 16384, sb + B_AGG);
                    rejoin();
                    if (b < NSLABX && wrp == 9) {
                        const float cc = __uint_as_float(lds32(sb + SM_C));
                        const uint32_t zt = sb + SM_PARK + 20480;
                        if (lane == 0) poll_ge(isQ ? &sc->l2 : &sc->a[b >> 3], isQ ? NLT : 11);
                        rejoin();
                        if (isQ) {
#pragma unroll 1
                            for (int n0 = 0; n0 < 16; n0 += 2) {
                                const int n = n0 + hi;
                                float4 v0 = make_float4(0.f, 0.f, 0.f, 0.f), v1 = v0;
#pragma unroll 4
                                for (int k = 0; k < NLC; k++) {
                                    float4* pl = reinterpret_cast<float4*>(sc->Lacc + k * 2048 + n * 128 + l16 * 8);
                                    const float4 a0 = __ldcg(pl), a1 = __ldcg(pl + 1);
                                    v0.x += a0.x; v0.y += a0.y; v0.z += a0.z; v0.w += a0.w; v1.x += a1.x; v1.y += a1.y; v1.z += a1.z; v1.w += a1.w;
                                }
                                const float k = safe_div(cc * 128.0f, half_sum(v0.x + v0.y + v0.z + v0.w + v1.x + v1.y + v1.z + v1.w));
                                sts128(zt + swz(n, l16), pack2(fmaf(v0.x, k, -cc), fmaf(v0.y, k, -cc)), pack2(fmaf(v0.z, k, -cc), fmaf(v0.w, k, -cc)),
                                       pack2(fmaf(v1.x, k, -cc), fmaf(v1.y, k, -cc)), pack2(fmaf(v1.z, k, -cc), fmaf(v1.w, k, -cc)));
                            }
                        } else {
#pragma unroll 1
                            for (int r = 0; r < 8; r++) {
                                const uint8_t* pb = sc->part + (b >> 3) * 11 * PART_BYTES;
                                const uint8_t* pu = pb + gq * PART_BYTES + 32768 + ((b & 7) * 32 + 4 * r + t) * 8;
                                float2 uu = __ldcg(reinterpret_cast<const float2*>(pu));
                                if (gq < 3) { const float2 u2 = __ldcg(reinterpret_cast<const float2*>(pu + 8 * PART_BYTES)); uu.x += u2.x; uu.y += u2.y; }
                                float a[8] = {0.f, 0.f, 0.f, 0.f, 0.f, 0.f, 0.f, 0.f};
                                const uint8_t* pp = pb + (b & 7) * 4096 + gq * 512 + (4 * r + t) * 16;
#pragma unroll 1
                                for (int k0 = 0; k0 < 12; k0 += 6) {
                                    uint4 v[6];
#pragma unroll
                                    for (int k = 0; k < 6; k++) { v[k] = make_uint4(0, 0, 0, 0); if (k < 5 || k0 == 0) v[k] = __ldcg(reinterpret_cast<const uint4*>(pp + (k0 + k) * PART_BYTES)); }
                                    sched_fence();
#pragma unroll
                                    for (int k = 0; k < 6; k++)
#pragma unroll
                                        for (int j = 0; j < 4; j++) { const uint32_t e = comp(v[k], j); a[2 * j] += blo(e); a[2 * j + 1] += bhi(e); }
                                }
                                float s0 = (a[0] + a[1]) + (a[4] + a[5]), s1 = (a[2] + a[3]) + (a[6] + a[7]);
#pragma unroll
                                for (int i = 4; i < 32; i *= 2) {
                                    uu.x += __shfl_xor_sync(~0u, uu.x, i); uu.y += __shfl_xor_sync(~0u, uu.y, i);
                                    s0 += __shfl_xor_sync(~0u, s0, i); s1 += __shfl_xor_sync(~0u, s1, i);
                                }
                                const float k0 = safe_div(cc * 4.0f, quad_sum(fmaf(s0, 1.0f / 32.0f, uu.x))), k1 = safe_div(cc * 4.0f, quad_sum(fmaf(s1, 1.0f / 32.0f, uu.y)));
                                const float c0 = fmaf(uu.x, k0, -cc), c1 = fmaf(uu.y, k1, -cc);
                                const uint32_t z0 = zt + swz(r, 2 * gq) + 4 * t;
                                sts32(z0, pack2(fmaf(a[0], k0, c0), fmaf(a[1], k0, c0))); sts32(z0 + 2048, pack2(fmaf(a[2], k1, c1), fmaf(a[3], k1, c1)));
                                sts32(z0 ^ 16, pack2(fmaf(a[4], k0, c0), fmaf(a[5], k0, c0))); sts32((z0 ^ 16) + 2048, pack2(fmaf(a[6], k1, c1), fmaf(a[7], k1, c1)));
                            }
                        }
                    }
                    }
                    { DERIVE_SC
                    const uint32_t lo16 = l16 * 16, base = sb + SM_RECV;
                    auto finish_row = [&](uint32_t ro, const float (&a)[8]) {
                        uint32_t dv;
                        asm volatile("ld.shared.u16 %0, [%1];" : "=r"(dv) : "r"(base + 11264 + (ro >> 6)));
                        const float k = blo(dv) * __uint_as_float(lds32(base + (SM_C - SM_RECV))) * (4.0f / KV_C0);
                        sts128(base - (SM_RECV - SM_PARK) + (ro & 0x380) + ((ro & ~0x3ffu) << 1) + ((lo16 & 128) << 3) + ((lo16 ^ (ro >> 3)) & 0x70),
                               pack2(a[0] * k, a[1] * k), pack2(a[2] * k, a[3] * k), pack2(a[4] * k, a[5] * k), pack2(a[6] * k, a[7] * k));
                    };
                    {
                        uint32_t bo = ((b < NSLABX ? (w ? GS * w - GS : 2 * GS) : 22 * w) + hi) * 128;
                        int rows = uni(b < NSLABX ? (w ? GS / 2 : 40 - GS) : w < 2 ? 11 : 10), n = -1;
                        __half2 h[4] = {h2(0), h2(0), h2(0), h2(0)};
#pragma unroll 1
                        for (;;) {
                            const uint4 en = lds128(base + bo);
                            uint4 v[8];
#pragma unroll
                            for (int k = 0; k < 8; k++)
                                v[k] = *reinterpret_cast<const uint4*>(sc->h16 + __byte_perm(comp(en, k >> 1), lo16, (k & 1) ? 0x5324 : 0x5104));
                            sched_fence();
                            if (n <= 0) {
                                if (n == 0) {
                                    float a[8];
#pragma unroll
                                    for (int j = 0; j < 4; j++) { a[2 * j] = __low2float(h[j]); a[2 * j + 1] = __high2float(h[j]); h[j] = h2(0); }
                                    finish_row(bo - 256, a);
                                    if (--rows == 0) break;
                                }
                                n = min(__reduce_max_sync(~0u, (int)lds32(base + bo + 124)), CAP);
                            }
                            sched_fence();
#pragma unroll
                            for (int j = 0; j < 4; j++)
                                h[j] = __hadd2(h[j], __hadd2(__hadd2(__hadd2(h2(comp(v[0], j)), h2(comp(v[1], j))), __hadd2(h2(comp(v[2], j)), h2(comp(v[3], j)))),
                                                             __hadd2(__hadd2(h2(comp(v[4], j)), h2(comp(v[5], j))), __hadd2(h2(comp(v[6], j)), h2(comp(v[7], j))))));
                            n = max(n - 8, 0);
                            bo = n ? bo + 16 : (bo & ~127u) + 256;
                        }
                    }
                    if (uni(lds32(base + (SM_BST + 8 - SM_RECV)))) {
                        DERIVE_SC
                        bar_sync(5, 96);
                        const int tot = INBOX / 4 + (int)__ldcg(&sc->ovf);
#pragma unroll 1
                        for (int lr = uni(w); lr < 80; lr += 3) {
                            if (uni(lds32(base + lr * 128 + 124)) <= CAP) continue;
                            float a[8] = {0.f, 0.f, 0.f, 0.f, 0.f, 0.f, 0.f, 0.f};
#pragma unroll 1
                            for (int k0 = 0; k0 < tot; k0 += 32) {
                                uint32_t e = 0;
                                if (k0 < INBOX / 4) e = lds32(base + 12288 + (k0 + lane) * 4);
                                else if (k0 + lane < tot) { const int2 e2 = __ldcg(&sc->ovfl[k0 + lane - INBOX / 4]); if (e2.x == b) e = e2.y; }
                                unsigned m = __ballot_sync(~0u, e && (int)(e >> 16) == lr);
#pragma unroll 1
                                while (m) {
                                    const unsigned m2 = m & (m - 1), mine = hi ? m2 : m;
                                    const uint32_t ee = __shfl_sync(~0u, e, __ffs(mine) - 1);
                                    const uint4 v = __ldcg(reinterpret_cast<const uint4*>(sc->h16 + lo16 + (mine ? (ee & 0xffff) << 8 : 0)));
#pragma unroll
                                    for (int j = 0; j < 4; j++) { const __half2 hh = h2(comp(v, j)); a[2 * j] += __low2float(hh); a[2 * j + 1] += __high2float(hh); }
                                    m = m2 & (m2 - 1);
                                }
                            }
#pragma unroll
                            for (int j = 0; j < 8; j++) a[j] += __shfl_xor_sync(~0u, a[j], 16);
                            finish_row(lr * 128, a);
                        }
                    }
                    fence_async_smem();
                    }
                    DERIVE_SC
                    st = uni(lds32(sb + SM_BST));
                    cmd = CMD_DONE;
                    bar_sync(5, 96);
                    if (bt == 32) { mbar_expect_tx(sb + B_AGG, 16384); if (lds32(sb + SM_BST + 8)) bulk_g2s(sb + SM_XR, x + b * 16384, 16384, sb + B_AGG); }
                }
                DERIVE_SC
                if (bt == 0) sts32(sb + SM_CMD, cmd);
                fence_async_smem();
                __syncwarp();
                if (lane == 0) mbar_arrive(sb + B_REQ);
                mbar_wait(sb + B_REQ, st >> 4);
            }
            DERIVE_SC
            const int cmd = uni(lds32(sb + SM_CMD));
            if (cmd == CMD_DONE) break;
            bar_sync(9, 128);
            const int nb = cmd >= CMD_W0 || (b >= NSLABX && b < 127) ? 4 : 2;
#pragma unroll 1
            for (int i = 0; i < nb; i += cmd == CMD_L ? 1 : 2) {
                DERIVE_SC
                const uint32_t ui = uni(i >> 1), qo = uni(b < NSLABX - 1 ? SM_RECV + 16384 : SM_XS);
                if (cmd >= CMD_W0) {
                    float acc[16];
                    const uint64_t da = desc_mn(SM_RECV) + ui * 64, db = desc_k(SM_PARK) + uni(cmd & 1) * 512;
                    wgmma_fence();
                    wgmma_ss32_m_i(acc, da, db);
#pragma unroll
                    for (int k = 1; k < 8; k++) wgmma_ss32_m(acc, da + k * 256, db + koff(k));
                    wgmma_commit();
                    wgmma_wait<0>();
                    pin<16>(acc);
                    const uint32_t d = sb + SM_XS + (8 * hi + (lane & 7)) * 256 + (2 * warp + ((lane >> 3) & 1)) * 16 + i * 64;
                    stsm4t(d, pack2(acc[0], acc[1]), pack2(acc[2], acc[3]), pack2(acc[4], acc[5]), pack2(acc[6], acc[7]));
                    stsm4t(d + 4096, pack2(acc[8], acc[9]), pack2(acc[10], acc[11]), pack2(acc[12], acc[13]), pack2(acc[14], acc[15]));
                } else if (!(i & 1)) {
                    float acc[8];
                    const uint64_t da = desc_k(SM_RECV) + ui * 1024, db = desc_k(qo);
                    wgmma_fence();
                    wgmma_ss16_k_i(acc, da, db);
#pragma unroll
                    for (int k = 1; k < 8; k++) wgmma_ss16_k(acc, da + koff(k), db + koff(k));
                    wgmma_commit();
                    const float2 pa = lds64f(sb + SM_SH + 8 * t), pb = lds64f(sb + SM_SH + 32 + 8 * t);
                    const float pr[4] = {pa.x, pa.y, pb.x, pb.y};
                    wgmma_wait<0>();
                    pin<8>(acc);
                    if (cmd == CMD_M) {
#pragma unroll
                        for (int j = 0; j < 4; j++) {
                            const int k = (j >> 1) * 4 + (j & 1);
                            const uint32_t uu = __float_as_uint(fmaxf(acc[k], acc[k + 2]));
                            atomicMax(&sc->Lmax[(j >> 1) * 8 + 2 * t + (j & 1)], (uu & 0x80000000u) ? ~uu : (uu | 0x80000000u));
                        }
                    } else {
                        const bool skip = b == 127 && warp < 3;
#pragma unroll
                        for (int k = 0; k < 8; k++) {
                            const float pv = pr[(k >> 2) * 2 + (k & 1)];
                            acc[k] = skip ? 0.f : ex2(acc[k] - pv);
                        }
                        stsm4t(sb + qo + 4096 + swz(8 * hi + (lane & 7), 2 * warp + ((lane >> 3) & 1)),
                               pack2(acc[0], acc[1]), pack2(acc[2], acc[3]), pack2(acc[4], acc[5]), pack2(acc[6], acc[7]));
                    }
                } else {
                    float acc[16];
                    const uint64_t da = desc_mn(SM_RECV) + ui * 1024, db = desc_k(qo + 4096);
                    wgmma_fence();
                    wgmma_ss16_m_i<0>(acc, da, db); wgmma_ss16_m_i<8>(acc, da + 64, db);
#pragma unroll
                    for (int k = 1; k < 4; k++) { wgmma_ss16_m<0>(acc, da + k * 256, db + koff(k)); wgmma_ss16_m<8>(acc, da + 64 + k * 256, db + koff(k)); }
                    wgmma_commit();
                    wgmma_wait<0>();
                    pin<16>(acc);
                    const uint32_t la = sb + (b < NSLABX ? SM_XS + 4096 : SM_PARK + ui * 8192) + (2 * t * 128 + 16 * warp + gq) * 4;
#pragma unroll
                    for (int k = 0; k < 16; k++) sts32(la + ((((k >> 2) & 1) * 8 + (k & 1)) * 128 + (k & 2) * 4 + (k >> 3) * 64) * 4, __float_as_uint(acc[k]));
                }
                if (tid == 256) {
                    const uint4 ps = lds128(sb + SM_PST);
                    const uint32_t sl = ps.y & 3;
                    if (ps.x - 8u < 38u && ps.x != 37 && !(ps.z | ps.w) && mbar_test(sb + B_EMPTY + 8 * sl, ((ps.y >> 2) & 1) ^ 1)) {
                        mbar_expect_tx(sb + B_FULL + 8 * sl, 32768);
                        bulk_g2s(sb + SM_RING + sl * SLOT, sc->kv + (rank * 313 + 8 * ps.x - 56) * 4096, 32768, sb + B_FULL + 8 * sl);
                        sts128(sb + SM_PST, ps.x + 1, ps.y + 1, 0, 0);
                    }
                }
                fence_async_smem();
                bar_sync(9, 128);
            }
        }
        cluster_wait();
        if (threadIdx.x == 256) mbar_wait_b(SB0 + ((blockIdx.x & 1) << 24) + B_FIN, 0);
        if (threadIdx.x == 288) {
            DERIVE_SC
            mbar_arrive_remote(mapa(sb + B_RFREE, rank ^ 1));
            mbar_wait(sb + B_W2, 0);
            __threadfence();
            if (atomicAdd(&sc->done, 1u) == NCTA - 1) {
                __threadfence();
                *h0 = 0ull;
#pragma unroll 1
                for (int i = 0; i < 64; i++) h1[16 * i] = 0ull;
                for (int i = 0; i < 12; i++) sc->a[i] = 0u;
                sc->b = 0u; sc->l1 = 0u; sc->l2 = 0u; sc->ovf = 0u; sc->ql = 0u; sc->cw = 0u; sc->done = 0u;
            }
        }
    }
}

}

extern "C" void kernel_launch(void* const* d_in, const int* in_sizes, int n_in, void* d_out, int out_size) {
    if (n_in != 9 || in_sizes[0] != NN * 128 || in_sizes[1] != EE || out_size != NN * 128) return;
    static Scratch* sc = nullptr;
    if (!sc) {
        cudaFuncSetAttribute(gps_kernel, cudaFuncAttributeMaxDynamicSharedMemorySize, SM_TOTAL);
        void* p = nullptr;
        cudaGetSymbolAddress(&p, g_raw);
        sc = reinterpret_cast<Scratch*>(((reinterpret_cast<uintptr_t>(p) + (2 << 20) - 1) & ~(uintptr_t)((2 << 20) - 1)) + 1024);
    }
    gps_kernel<<<NCTA, 384, SM_TOTAL>>>((const uint8_t*)d_in[0], (const int*)d_in[1], (const int*)d_in[2], (const __nv_bfloat16*)d_in[3],
                                        (const uint8_t*)d_in[4], (const uint8_t*)d_in[5], (const uint8_t*)d_in[6], (const uint8_t*)d_in[7],
                                        (const uint8_t*)d_in[8], (uint8_t*)d_out, sc,
                                        reinterpret_cast<unsigned long long*>(sc) - 128, sc->h1);
}
```
